```python
import torch

def _softmax(x, axis=-1):
    return torch.softmax(x, dim=axis)
def _gelu(x):
    return torch.nn.functional.gelu(x, approximate="tanh")
def _silu(x):
    return torch.nn.functional.silu(x)
def _sigmoid(x):
    return torch.sigmoid(x)
def _layernorm(x, axis=-1, eps=1e-5):
    m = x.mean(dim=axis, keepdim=True)
    v = x.var(dim=axis, keepdim=True, unbiased=False)
    return (x - m) / torch.sqrt(v + eps)
def _scatter_add(tgt, idx, src, axis=0):
    return tgt.clone().index_add_(axis, idx, src)
def _segment_sum(src, seg, n):
    out = torch.zeros((n,) + src.shape[1:], dtype=src.dtype)
    return out.index_add_(0, seg, src)
def _pad(x, pw):
    flat = tuple(v for pair in reversed(pw) for v in pair)
    return torch.nn.functional.pad(x, flat)

kernel_name = 'standalone__cheap_equivariant_egnn__graph'

def setup_inputs():

    _w = (lambda a: (lambda t: t.to(torch.bfloat16) if t.is_floating_point() else t)(torch.as_tensor(a)))
    N, deg, D, De = 50000, 16, 64, max(16, 1)
    E = N * deg
    return {
        "h": _w((lambda *s: torch.randn(*s, dtype=torch.bfloat16) * 0.2)(N, D)),
        "pos": _w((lambda *s: torch.randn(*s, dtype=torch.bfloat16) * 0.8)(N, 3)),
        "e_attr": _w((lambda *s: torch.randn(*s, dtype=torch.bfloat16) * 0.8)(E, De)),
        "src": _w((lambda lo, hi, *s: torch.randint(lo, hi, s))(0, N, E).to(torch.int64)),
        "dst": _w((lambda lo, hi, *s: torch.randint(lo, hi, s))(0, N, E).to(torch.int64)),
        "w_e": _w(0.1 * (lambda *s: torch.randn(*s, dtype=torch.bfloat16) * 0.8)(2 * D + 1 + De, D)),
        "w_x": _w(0.1 * (lambda *s: torch.randn(*s, dtype=torch.bfloat16) * 0.2)(D, 1)),
        "w_h": _w(0.1 * (lambda *s: torch.randn(*s, dtype=torch.bfloat16) * 0.2)(2 * D, D)),
    }

def reference(h, pos, e_attr, src, dst, w_e, w_x, w_h):
    N, D = h.shape[0], h.shape[1]
    diff = pos[dst] - pos[src]
    dist2 = torch.sum(diff * diff, axis=-1, keepdims=True)
    e_in = torch.concatenate([h[dst], h[src], dist2, e_attr], axis=-1)
    m_ij = _silu(e_in @ w_e)
    coord_scale = m_ij @ w_x
    pos_new = pos + _segment_sum(diff * coord_scale, dst, N)
    m_i = _segment_sum(m_ij, dst, N)
    h_new = h + _silu(torch.concatenate([h, m_i], axis=-1) @ w_h)
    return h_new, pos_new
```

```cpp
#include <cuda_runtime.h>
#include <cuda_bf16.h>
#include <cuda_fp16.h>
#include <cuda.h>
#include <stdint.h>

#define PFA 8
#define HPF 99
#define CHK 8192
#define EPOL "evict_unchanged"
#define XPOL 2
#define ORD 0
#define WIN 6
#define PDELAY 0
#define UNR 1
#define DEF 1
namespace {

constexpr int G = 132;
constexpr int NT = 512;
constexpr int CAP = 48;
constexpr int FS = 384;
constexpr uint32_t sb = 1024;

constexpr uint32_t A_RING = sb;
constexpr uint32_t A_PT = A_RING + 16 * 5120;
constexpr uint32_t A_W3 = A_PT + 49152;
constexpr uint32_t A_TAB = A_W3 + 2048;
constexpr uint32_t A_IN = A_TAB + 37888;
constexpr uint32_t A_WD = A_IN + G * FS + 512;
constexpr uint32_t A_WD2 = A_WD + 256;
constexpr uint32_t A_BAR = A_WD2 + 1024;
constexpr uint32_t A_MISC = A_BAR + 144;
constexpr uint32_t A_DH = A_MISC + 32;
constexpr uint32_t A_CNT = A_DH + 256;
constexpr uint32_t A_POSH = A_CNT + 2176;
constexpr uint32_t A_POSB = A_POSH + 3072;
constexpr uint32_t A_ROWS = A_POSB + 2304;
constexpr uint32_t A_LEN = A_ROWS + 768;
constexpr uint32_t A_END = A_LEN + 192;
constexpr int SMEM = A_END - sb;
static_assert(SMEM <= 232448 && A_TAB % 1024 == 0 && A_IN % 1024 == 0 && A_PT % 1024 == 0 && A_WD2 % 128 == 0, "smem");
constexpr int NX = 384, CH = NX * 16;
constexpr uint32_t A_QS = A_RING, A_W = A_QS + 49152, A_SA = A_IN, A_SB = A_SA + (G + 1) * 128, A_SRC = A_TAB;
__host__ __device__ constexpr uint32_t a_dst(int k) { return k < 2 ? A_W + 16384 + k * CH : A_SRC + (k + 2) * CH; }
static_assert(a_dst(1) + CH <= A_PT && a_dst(3) + CH <= A_IN && A_SB + (G + 1) * 256 <= A_WD, "staging");
constexpr uint32_t BAR_C = A_BAR, BAR_T = BAR_C + 64, BAR_W = A_BAR + 112, BAR_U = A_BAR + 120, BAR_Q = A_BAR + 128, BAR_X = A_BAR + 136;

struct Scratch {
  uint4 q[(G * 384 + 64) * 8];
  uint4 xa[G * G * 8];
  uint4 xb[G * G * 16];
  uint2 xe[G * G * 32];
  uint32_t ep[G * 32];
  uint32_t cnt[32];
};
__device__ __align__(256) Scratch g_s;
#define STAMP(k)

struct Maps { CUtensorMap m[9]; };
constexpr int TM_H = 0, TM_WE = 128, TM_WH = 256, TM_Q = 384, TM_O = 512, TM_O2 = 640, TM_XA = 768, TM_XB = 896, TM_W3 = 1024;
struct Params {
  const int* dst; const int* src; int E, EPC, force_slow, NPC; Scratch* s; int N; uint32_t magic;
  const uint16_t* h; const uint16_t* pos; const uint16_t* ea; const uint16_t* we; const uint16_t* wx; const uint16_t* wh; uint16_t* out;
};

#define R32(d) "+f"(d[0]),"+f"(d[1]),"+f"(d[2]),"+f"(d[3]),"+f"(d[4]),"+f"(d[5]),"+f"(d[6]),"+f"(d[7]),"+f"(d[8]),"+f"(d[9]),"+f"(d[10]),"+f"(d[11]),"+f"(d[12]),"+f"(d[13]),"+f"(d[14]),"+f"(d[15]),"+f"(d[16]),"+f"(d[17]),"+f"(d[18]),"+f"(d[19]),"+f"(d[20]),"+f"(d[21]),"+f"(d[22]),"+f"(d[23]),"+f"(d[24]),"+f"(d[25]),"+f"(d[26]),"+f"(d[27]),"+f"(d[28]),"+f"(d[29]),"+f"(d[30]),"+f"(d[31])
#define S32 "{%0,%1,%2,%3,%4,%5,%6,%7,%8,%9,%10,%11,%12,%13,%14,%15,%16,%17,%18,%19,%20,%21,%22,%23,%24,%25,%26,%27,%28,%29,%30,%31}"
#define R16(d) "+f"(d[0]),"+f"(d[1]),"+f"(d[2]),"+f"(d[3]),"+f"(d[4]),"+f"(d[5]),"+f"(d[6]),"+f"(d[7]),"+f"(d[8]),"+f"(d[9]),"+f"(d[10]),"+f"(d[11]),"+f"(d[12]),"+f"(d[13]),"+f"(d[14]),"+f"(d[15])
#define S16 "{%0,%1,%2,%3,%4,%5,%6,%7,%8,%9,%10,%11,%12,%13,%14,%15}"
#define DI __device__ __forceinline__

constexpr uint64_t DHI = (64ull << 32) | (1ull << 62);
template<int SD> DI void ss64(float (&d)[32], uint64_t da, uint64_t db) {
  asm volatile("wgmma.mma_async.sync.aligned.m64n64k16.f32.bf16.bf16 " S32 ", %32, %33, %34, 1, 1, 0, 1;" : R32(d) : "l"(da), "l"(db), "n"(SD)); }
template<int SD> DI void ss32(float (&d)[16], uint64_t da, uint64_t db) {
  asm volatile("wgmma.mma_async.sync.aligned.m64n32k16.f32.bf16.bf16 " S16 ", %16, %17, %18, 1, 1, 0, 1;" : R16(d) : "l"(da), "l"(db), "n"(SD)); }
DI void wg_fence() { asm volatile("wgmma.fence.sync.aligned;" ::: "memory"); }
DI void wg_commit() { asm volatile("wgmma.commit_group.sync.aligned;" ::: "memory"); }
DI void wg_wait0() { asm volatile("wgmma.wait_group.sync.aligned 0;" ::: "memory"); }
DI void fence_regs(float (&d)[32]) { asm volatile("" : R32(d) :: "memory"); }
DI void fence_regs(float (&d)[16]) { asm volatile("" : R16(d) :: "memory"); }
DI void proxy_fence() { asm volatile("fence.proxy.async.shared::cta;" ::: "memory"); }
DI void hmma(uint32_t& d0, uint32_t& d1, const uint32_t* a, uint32_t b0, uint32_t b1) {
  asm("mma.sync.aligned.m16n8k16.row.col.f16.f16.f16.f16 {%0,%1}, {%2,%3,%4,%5}, {%6,%7}, {%0,%1};" : "+r"(d0), "+r"(d1) : "r"(a[0]), "r"(a[1]), "r"(a[2]), "r"(a[3]), "r"(b0), "r"(b1)); }
DI uint64_t pol_first() { uint64_t r; asm("createpolicy.fractional.L2::evict_first.b64 %0, 1.0;" : "=l"(r)); return r; }
DI float tanh_ap(float x) { float y; asm("tanh.approx.f32 %0, %1;" : "=f"(y) : "f"(x)); return y; }
DI float silu(float x) { const float y = 0.5f * x; return fmaf(y, tanh_ap(y), y); }
DI uint32_t pack_bf16(float lo, float hi) { uint32_t r; asm("cvt.rn.bf16x2.f32 %0, %1, %2;" : "=r"(r) : "f"(hi), "f"(lo)); return r; }
DI uint32_t pack_f16(float lo, float hi) { uint32_t r; asm("cvt.rn.f16x2.f32 %0, %1, %2;" : "=r"(r) : "f"(hi), "f"(lo)); return r; }
DI float bf_lo(uint32_t v) { return __uint_as_float(v << 16); }
DI float bf_hi(uint32_t v) { return __uint_as_float(v & 0xFFFF0000u); }
DI uint32_t b2h(uint32_t v) { return pack_f16(bf_lo(v), bf_hi(v)); }
DI uint32_t h2b(uint32_t v) { const float2 f = __half22float2(*(const __half2*)&v); return pack_bf16(f.x, f.y); }
DI uint32_t hadd(uint32_t a, uint32_t b) { uint32_t r; asm("add.rn.f16x2 %0, %1, %2;" : "=r"(r) : "r"(a), "r"(b)); return r; }
DI uint32_t hsub(uint32_t a, uint32_t b) { uint32_t r; asm("sub.rn.f16x2 %0, %1, %2;" : "=r"(r) : "r"(a), "r"(b)); return r; }
DI uint32_t hfma(uint32_t a, uint32_t b, uint32_t c) { uint32_t r; asm("fma.rn.f16x2 %0, %1, %2, %3;" : "=r"(r) : "r"(a), "r"(b), "r"(c)); return r; }
DI uint32_t hsilu(uint32_t y) { uint32_t t; asm("tanh.approx.f16x2 %0, %1;" : "=r"(t) : "r"(y)); return hfma(y, t, y); }
DI uint32_t badd(uint32_t a, uint32_t b) { uint32_t r; asm("add.rn.bf16x2 %0, %1, %2;" : "=r"(r) : "r"(a), "r"(b)); return r; }
DI uint32_t bhalf(uint32_t v) { uint32_t r; asm("mul.rn.bf16x2 %0, %1, %2;" : "=r"(r) : "r"(v), "r"(0x3F003F00u)); return r; }
DI uint32_t amax2(uint32_t mx, uint32_t v) { return __vmaxu2(mx, v & 0x7FFF7FFFu); }
DI uint32_t amax_warp(uint32_t mx) { return __reduce_max_sync(~0u, max(mx & 0xFFFF, mx >> 16)); }
DI void mbar_wait(uint32_t bar, uint32_t parity) {
  asm volatile("{.reg .pred p; .reg .u32 c; mov.u32 c, 0;\n"
    "LW_%=: mbarrier.try_wait.parity.shared::cta.b64 p, [%0], %1;\n"
    "@p bra.uni LD_%=;\n add.u32 c, c, 1; setp.lt.u32 p, c, 20000000;\n @p bra.uni LW_%=;\n trap;\n LD_%=:}" :: "r"(bar), "r"(parity) : "memory");
}
DI void mbar_arrive(uint32_t bar) { asm volatile("mbarrier.arrive.shared::cta.b64 _, [%0];" :: "r"(bar) : "memory"); }
DI void bar_sync(int id, int n) { asm volatile("bar.sync %0, %1;" :: "r"(id), "r"(n) : "memory"); }
DI void bar_arrive(int id, int n) { asm volatile("bar.arrive %0, %1;" :: "r"(id), "r"(n) : "memory"); }
DI void sts128(uint32_t a, uint32_t x, uint32_t y, uint32_t z, uint32_t w) { asm volatile("st.shared.v4.u32 [%0], {%1,%2,%3,%4};" :: "r"(a), "r"(x), "r"(y), "r"(z), "r"(w) : "memory"); }
DI void sts64(uint32_t a, uint32_t x, uint32_t y) { asm volatile("st.shared.v2.u32 [%0], {%1,%2};" :: "r"(a), "r"(x), "r"(y) : "memory"); }
DI void sts32(uint32_t a, uint32_t x) { asm volatile("st.shared.u32 [%0], %1;" :: "r"(a), "r"(x) : "memory"); }
DI void sts16(uint32_t a, uint32_t x) { asm volatile("st.shared.u16 [%0], %1;" :: "r"(a), "h"((uint16_t)x) : "memory"); }
DI void sts32p(uint32_t a, uint32_t x, bool p) { asm volatile("{.reg .pred p; setp.ne.b32 p, %2, 0; @p st.shared.u32 [%0], %1;}" :: "r"(a), "r"(x), "r"((int)p) : "memory"); }
DI void sts16p(uint32_t a, uint32_t x, bool p) { asm volatile("{.reg .pred p; setp.ne.b32 p, %2, 0; @p st.shared.u16 [%0], %1;}" :: "r"(a), "h"((uint16_t)x), "r"((int)p) : "memory"); }
DI void lds128(uint32_t* v, uint32_t a) { asm volatile("ld.shared.v4.u32 {%0, %1, %2, %3}, [%4];" : "=r"(v[0]), "=r"(v[1]), "=r"(v[2]), "=r"(v[3]) : "r"(a) : "memory"); }
DI void lds64(uint32_t& x, uint32_t& y, uint32_t a) { asm volatile("ld.shared.v2.u32 {%0, %1}, [%2];" : "=r"(x), "=r"(y) : "r"(a) : "memory"); }
DI uint32_t lds32(uint32_t a) { uint32_t x; asm volatile("ld.shared.u32 %0, [%1];" : "=r"(x) : "r"(a) : "memory"); return x; }
DI uint32_t lds16(uint32_t a) { uint32_t x; asm volatile("ld.shared.u16 %0, [%1];" : "=r"(x) : "r"(a) : "memory"); return x; }
DI uint32_t atoms_add(uint32_t a, uint32_t v) { uint32_t r; asm volatile("atom.shared.add.u32 %0, [%1], %2;" : "=r"(r) : "r"(a), "r"(v) : "memory"); return r; }
DI uint32_t atoms_incp(uint32_t a, bool p) { uint32_t r = 0; asm volatile("{.reg .pred p; setp.ne.b32 p, %2, 0; @p atom.shared.add.u32 %0, [%1], 1;}" : "+r"(r) : "r"(a), "r"((int)p) : "memory"); return r; }
DI uint32_t ldg_poll(const void* a) { uint32_t x; asm volatile("ld.relaxed.gpu.global.u32 %0, [%1];" : "=r"(x) : "l"(a) : "memory"); return x; }
DI uint2 ldg_poll2(const void* a) { uint2 x; asm volatile("ld.relaxed.gpu.global.v2.u32 {%0, %1}, [%2];" : "=r"(x.x), "=r"(x.y) : "l"(a) : "memory"); return x; }
DI void bulk_load(uint32_t dst, const void* src, uint32_t bytes, uint32_t bar) {
  asm volatile("cp.async.bulk.shared::cluster.global.mbarrier::complete_tx::bytes.L2::cache_hint [%0], [%1], %2, [%3], %4;" :: "r"(dst), "l"(src), "r"(bytes), "r"(bar), "l"(pol_first()) : "memory"); }
DI void mbar_expect(uint32_t bar, uint32_t bytes) { asm volatile("mbarrier.arrive.expect_tx.shared::cta.b64 _, [%0], %1;" :: "r"(bar), "r"(bytes) : "memory"); }
DI void mbar_init(uint32_t bar, int n) { asm volatile("mbarrier.init.shared::cta.b64 [%0], %1;" :: "r"(bar), "r"(n) : "memory"); }
DI void tma_load(uint32_t dst, uint64_t tm, int row, uint32_t bar) {
  asm volatile("cp.async.bulk.tensor.2d.shared::cluster.global.mbarrier::complete_tx::bytes.L2::cache_hint [%0], [%1, {%3, %4}], [%2], %5;" :: "r"(dst), "l"(tm), "r"(bar), "r"(0), "r"(row), "l"(pol_first()) : "memory"); }
DI void tma_store(uint64_t tm, int col, int row, uint32_t src) {
  asm volatile("cp.async.bulk.tensor.2d.global.shared::cta.bulk_group [%0, {%2, %3}], [%1];" :: "l"(tm), "r"(src), "r"(col), "r"(row) : "memory"); }
DI void tma_store_x(uint64_t tm, int col, uint32_t src) {
  if (XPOL & 1) asm volatile("cp.async.bulk.tensor.2d.global.shared::cta.bulk_group.L2::cache_hint [%0, {%2, 0}], [%1], %3;" :: "l"(tm), "r"(src), "r"(col), "l"(pol_first()) : "memory");
  else tma_store(tm, col, 0, src); }
DI void bulk_commit() { asm volatile("cp.async.bulk.commit_group;" ::: "memory"); }
DI void stsm4(uint32_t a, uint32_t x, uint32_t y, uint32_t z, uint32_t w) { asm volatile("stmatrix.sync.aligned.m8n8.x4.shared.b16 [%0], {%1,%2,%3,%4};" :: "r"(a), "r"(x), "r"(y), "r"(z), "r"(w) : "memory"); }
DI void ldsm4(uint32_t* v, uint32_t a) { asm volatile("ldmatrix.sync.aligned.m8n8.x4.shared.b16 {%0,%1,%2,%3}, [%4];" : "=r"(v[0]), "=r"(v[1]), "=r"(v[2]), "=r"(v[3]) : "r"(a) : "memory"); }
DI void ldsm4t(uint32_t& x, uint32_t& y, uint32_t& z, uint32_t& w, uint32_t a) { asm volatile("ldmatrix.sync.aligned.m8n8.x4.trans.shared.b16 {%0,%1,%2,%3}, [%4];" : "=r"(x), "=r"(y), "=r"(z), "=r"(w) : "r"(a) : "memory"); }

__device__ __noinline__ void slow_path(const Params& p) {
  const int lane = threadIdx.x & 31, wid = threadIdx.x >> 5;
  const uint32_t ab = sb + wid * (24 * 528);
  const uint32_t* we = (const uint32_t*)p.we;
  const int nend = min(p.N, (blockIdx.x + 1) * p.NPC);
  auto rowmul = [&](uint32_t hv, const uint32_t* w, float& y0, float& y1) {
#pragma unroll 4
    for (int k = 0; k < 32; k++) {
      const uint32_t hk = __shfl_sync(~0u, hv, k), wa = __ldg(w + 2 * k * 32 + lane), wb = __ldg(w + (2 * k + 1) * 32 + lane);
      y0 = fmaf(bf_lo(hk), bf_lo(wa), fmaf(bf_hi(hk), bf_lo(wb), y0)); y1 = fmaf(bf_lo(hk), bf_hi(wa), fmaf(bf_hi(hk), bf_hi(wb), y1));
    }
  };
  auto act = [](float x) { return x / (1.f + __expf(-x)); };
  auto hrow = [&](int n) { return __ldg(p.h + (size_t)n * 64 + 2 * lane) | ((uint32_t)__ldg(p.h + (size_t)n * 64 + 2 * lane + 1) << 16); };
  const uint32_t wdv = __ldg(we + 128 * 32 + lane), wxv = __ldg((const uint32_t*)p.wx + lane);
  for (int nb = blockIdx.x * p.NPC + wid * 24; nb < nend; nb += 384) {
    const int cnt = min(24, nend - nb);
    for (int n = 0; n < cnt; n++) {
      float y0 = 0.f, y1 = 0.f; rowmul(hrow(nb + n), we, y0, y1);
      sts64(ab + n * 528 + lane * 8, 0, 0); sts64(ab + n * 528 + 256 + lane * 8, __float_as_uint(y0), __float_as_uint(y1));
      if (lane < 4) sts32(ab + n * 528 + 512 + lane * 4, 0);
    }
    __syncwarp();
    for (int base = 0; base < p.E; base += 32) {
      const uint32_t dl = base + lane < p.E ? (uint32_t)(__ldg(p.dst + base + lane) - nb) : 0xFFFFFFFFu;
      uint32_t mk = __ballot_sync(~0u, dl < (uint32_t)cnt);
      while (mk) {
        const int l = __ffs(mk) - 1; mk &= mk - 1;
        const int e = base + l, n = __shfl_sync(~0u, dl, l), s = __ldg(p.src + e);
        const uint32_t a = ab + n * 528;
        float df = 0.f;
        if (lane < 3) df = bf_lo(pack_bf16(bf_lo(__ldg(p.pos + (size_t)(nb + n) * 3 + lane)) - bf_lo(__ldg(p.pos + (size_t)s * 3 + lane)), 0.f));
        float d2 = df * df; d2 += __shfl_xor_sync(~0u, d2, 1); d2 += __shfl_xor_sync(~0u, d2, 2); d2 = __shfl_sync(~0u, d2, 0);
        uint32_t x0, x1; lds64(x0, x1, a + 256 + lane * 8);
        float y0 = fmaf(d2, bf_lo(wdv), __uint_as_float(x0)), y1 = fmaf(d2, bf_hi(wdv), __uint_as_float(x1));
        rowmul(hrow(s), we + 64 * 32, y0, y1);
        for (int k = 0; k < 16; k++) { const float ev = bf_lo(__ldg(p.ea + (size_t)e * 16 + k)); const uint32_t w = __ldg(we + (129 + k) * 32 + lane); y0 = fmaf(ev, bf_lo(w), y0); y1 = fmaf(ev, bf_hi(w), y1); }
        y0 = act(y0); y1 = act(y1);
        float c = y0 * bf_lo(wxv) + y1 * bf_hi(wxv);
#pragma unroll
        for (int o = 16; o; o >>= 1) c += __shfl_xor_sync(~0u, c, o);
        lds64(x0, x1, a + lane * 8);
        sts64(a + lane * 8, __float_as_uint(__uint_as_float(x0) + y0), __float_as_uint(__uint_as_float(x1) + y1));
        if (lane < 3) sts32(a + 512 + lane * 4, __float_as_uint(fmaf(c, df, __uint_as_float(lds32(a + 512 + lane * 4)))));
      }
    }
    __syncwarp();
    for (int n = 0; n < cnt; n++) {
      const uint32_t hv = hrow(nb + n); uint32_t x0, x1; lds64(x0, x1, ab + n * 528 + lane * 8);
      float y0 = 0.f, y1 = 0.f; rowmul(hv, (const uint32_t*)p.wh, y0, y1); rowmul(pack_bf16(__uint_as_float(x0), __uint_as_float(x1)), (const uint32_t*)p.wh + 64 * 32, y0, y1);
      const uint32_t o = badd(hv, pack_bf16(act(y0), act(y1)));
      p.out[(size_t)(nb + n) * 64 + 2 * lane] = (uint16_t)o; p.out[(size_t)(nb + n) * 64 + 2 * lane + 1] = (uint16_t)(o >> 16);
      if (lane < 3) p.out[(size_t)p.N * 64 + (size_t)(nb + n) * 3 + lane] = (uint16_t)pack_bf16(bf_lo(__ldg(p.pos + (size_t)(nb + n) * 3 + lane)) + __uint_as_float(lds32(ab + n * 528 + 512 + lane * 4)), 0.f);
    }
    __syncwarp();
  }
}

DI void tail_loads(const Params& p, uint64_t tmb, uint32_t id) {
  int cta; asm volatile("mov.u32 %0, %%ctaid.x;" : "=r"(cta));
  const int node0 = cta * p.NPC, nloc = min(p.NPC, p.N - node0);
  if (id != 63) { if (nloc > 0) asm volatile("cp.async.bulk.prefetch.L2.global [%0], %1;" :: "l"(p.h + (size_t)node0 * 64), "r"(nloc * 128) : "memory"); }
  else {
    proxy_fence();
    mbar_expect(BAR_U, 65536);
#pragma unroll 1
    for (int b = 0; b < 8; b++) tma_load(b < 2 ? A_TAB + b * 8192 : A_IN + (b - 2) * 8192, tmb + (b < 2 ? TM_WH : TM_H), b < 2 ? b * 64 : node0 + (b - 2) * 64, BAR_U);
  }
}

__global__ void __launch_bounds__(NT, 1) egnn_kernel(const __grid_constant__ Params p, const __grid_constant__ Maps maps) {
  extern __shared__ __align__(1024) unsigned char smraw[];
  const int tid = threadIdx.x, cta = blockIdx.x;
  const int e0 = cta * p.EPC, nb = max(0, min(p.EPC, p.E - e0)) * 4;
  STAMP(0);
  auto load_idx = [&](int c) {
    const int o = (c & 3) * CH, n = max(0, min(CH, nb - o));
    mbar_expect(BAR_C + c * 8, n);
    if (n) bulk_load(c < 4 ? a_dst(c) : A_SRC + o, (const char*)((c < 4 ? p.dst : p.src) + e0) + o, n, BAR_C + c * 8);
  };
  if (tid == 480 && !p.force_slow) {
#pragma unroll
    for (int c = 0; c < 4; c++) mbar_init(BAR_C + c * 8, 1);
    asm volatile("fence.mbarrier_init.release.cluster;" ::: "memory");
#pragma unroll
    for (int c = 0; c < 4; c++) load_idx(c);
  }
  if (p.force_slow) { slow_path(p); return; }
  uint32_t ep = ldg_poll(p.s->ep + cta * 32), tgb;
  const uint64_t tmb = (uint64_t)&maps;
  const int lane = tid & 31, wid = __shfl_sync(~0u, tid >> 5, 0), g8 = lane >> 2, q = lane & 3;
  const int w = wid & 3;
  const uint32_t frag = (w * 16 + (lane & 15)) * 128 + (((lane >> 4) ^ (lane & 7)) << 4), pa = A_POSH + (w * 16 + g8) * 8 + q * 2;
  float a0[32], a1[32];
  __half2 mx = __float2half2_rn(0.f);
  auto mma = [&](float (&acc)[32], int b, int blk) {
    const uint64_t da = DHI | ((A_PT + blk * 8192) >> 4), db = DHI | ((A_W + b * 8192) >> 4);
    wg_fence();
    ss64<0>(acc, da, db); ss64<1>(acc, da + 2, db + 128); ss64<1>(acc, da + 4, db + 256); ss64<1>(acc, da + 6, db + 384);
    wg_commit();
  };
  auto epi = [&](float (&acc)[32], int b, int blk) {
    uint32_t o[16];
#pragma unroll
    for (int j = 0; j < 16; j++) o[j] = pack_f16(acc[2 * j], acc[2 * j + 1]);
    if (b) {
#pragma unroll
      for (int j = 0; j < 16; j++) mx = __hmax2_nan(mx, __habs2(*(const __half2*)&o[j]));
    } else {
#pragma unroll
      for (int r = 0; r < 2; r++) {
        const uint32_t T = __byte_perm(lds16(pa + blk * 512 + r * 64), 0, 0x4140);
#pragma unroll
        for (int j = 0; j < 4; j++) o[2 * j + r] &= 0xFFFCFFFCu;
        const uint32_t S = o[r] + o[2 + r] * 4 + o[4 + r] * 16 + o[6 + r] * 64;
        const uint32_t X = (T - S) & 255, Y = X | ((T - ((S + X) & 0xFFFF0000u)) & 0x00FF0000u);
#pragma unroll
        for (int j = 0; j < 4; j++) o[2 * j + r] |= (Y >> (2 * j)) & 0x00030003u;
      }
    }
    const uint32_t a = (b ? A_PT : A_QS) + blk * 8192 + frag;
#pragma unroll
    for (int j = 0; j < 4; j++) stsm4(a ^ (j << 5), o[4 * j], o[4 * j + 1], o[4 * j + 2], o[4 * j + 3]);
  };
  if (wid >= 12) {
    const int node0 = cta * p.NPC, nloc = max(0, min(p.NPC, p.N - node0)), t = tid - 384;
    if (wid == 14 && lane == 0) {
#pragma unroll
      for (int c = 4; c < 18; c++) mbar_init(BAR_C + c * 8, 1);
      asm volatile("fence.mbarrier_init.release.cluster;" ::: "memory");
#pragma unroll
      for (int b = 0; b < 6; b++) mbar_expect(BAR_T + b * 8, 8192);
      mbar_expect(BAR_W, 2 * 8192 + 2048 + 256);
      if ((uint32_t)__cvta_generic_to_shared(smraw) != sb) __trap();
    }
    if (wid == 13 && lane < 9) asm volatile("prefetch.tensormap [%0];" :: "l"(tmb + lane * 128));
    uint32_t ps[12];
#pragma unroll
    for (int k = 0; k < 4; k++) {
      ps[3 * k] = ps[3 * k + 1] = ps[3 * k + 2] = 0;
      asm volatile("{.reg .pred p; setp.lt.s32 p, %4, %5;\n @p ld.global.nc.u16 %0, [%3];\n @p ld.global.nc.u16 %1, [%3+2];\n @p ld.global.nc.u16 %2, [%3+4];}"
        : "+r"(ps[3 * k]), "+r"(ps[3 * k + 1]), "+r"(ps[3 * k + 2]) : "l"(p.pos + (size_t)(node0 + t + 96 * k) * 3), "r"(t + 96 * k), "r"(w < 3 ? p.N - node0 : 0));
    }
    __syncthreads();
    auto load_h = [&](int b) { tma_load(A_PT + b * 8192, tmb + TM_H, node0 + b * 64, BAR_T + b * 8); };
    if (w == 3) {
      if (lane == 0) {
        tma_load(A_W, tmb + TM_WE, 64, BAR_W); tma_load(A_W + 8192, tmb + TM_WE, 0, BAR_W); tma_load(A_W3, tmb + TM_W3, 129, BAR_W);
        bulk_load(A_WD, p.we + 128 * 64, 128, BAR_W); bulk_load(A_WD + 128, p.wx, 128, BAR_W);
#pragma unroll 1
        for (int c = 4; c < 8 + WIN; c++) { if (c >= WIN) mbar_wait(BAR_C + (c - WIN) * 8, 0); if (c < 8) load_idx(c); else load_h(c - 8); }
      }
      __syncwarp();
    } else {
      uint32_t mp = 0;
#pragma unroll
      for (int k = 0; k < 4; k++) {
        const int n = t + 96 * k;
        sts64(A_POSH + n * 8, pack_f16(bf_lo(ps[3 * k]), bf_lo(ps[3 * k + 1])), pack_f16(bf_lo(ps[3 * k + 2]), 1.f));
        sts16(A_POSB + n * 6, ps[3 * k]); sts16(A_POSB + n * 6 + 2, ps[3 * k + 1]); sts16(A_POSB + n * 6 + 4, ps[3 * k + 2]);
        mp = amax2(amax2(mp, ps[3 * k] | (ps[3 * k + 1] << 16)), ps[3 * k + 2]);
      }
      mbar_wait(BAR_W, 0);
#pragma unroll
      for (int k = 0; k < 11; k++) if (k < 10 || w < 2) { uint32_t v[4]; const uint32_t a = A_W + (t + k * 96) * 16; lds128(v, a); sts128(a, bhalf(v[0]), bhalf(v[1]), bhalf(v[2]), bhalf(v[3])); }
      const uint32_t wd = lds32(A_WD + lane * 4), md = amax_warp(wd & 0x7FFF7FFFu);
      mp = amax_warp(mp);
      bool bad = md - 0x3B00 > 0x680 || !(bf_lo(mp) * bf_lo(mp) * bf_lo(md) < 6000.f) || (mp < 0x3B80 && (w + 1) * 32 <= nloc);
      if (w < 2) {
        uint32_t mw = 0;
#pragma unroll
        for (int k = 0; k < 2; k++) { uint32_t v[4]; const uint32_t a = A_W3 + (t + k * 64) * 16; lds128(v, a);
          sts128(a, b2h(bhalf(v[0])), b2h(bhalf(v[1])), b2h(bhalf(v[2])), b2h(bhalf(v[3]))); mw = amax2(amax2(amax2(amax2(mw, v[0]), v[1]), v[2]), v[3]); }
        bad |= amax_warp(mw) - 0x3B00 > 0x680;
      } else {
#pragma unroll
        for (int r = 0; r < 8; r++) sts32(A_WD2 + r * 128 + ((lane * 4) ^ (r << 4)), (r & 1) ? 0 : r == 6 ? 0xF753F753u : b2h(bhalf(wd)));
        const uint32_t x = lds32(A_WD + 128 + lane * 4), ex = min(max(amax_warp(x & 0x7FFF7FFFu) >> 7, 20u), 230u);
        const float sc = __uint_as_float((252 - ex) << 23);
        sts32(A_WD + 128 + lane * 4, pack_f16(bf_lo(x) * sc, bf_hi(x) * sc)); sts32(A_MISC + 12, (ex + 2) << 23);
      }
      if (bad) sts32(A_MISC, 1);
      proxy_fence();
    }
    bar_sync(6, 128);
    if (w == 0) STAMP(16);
    auto begin = [&](float (&acc)[32], int b) {
      mbar_wait(BAR_T + b * 8, 0);
      if (tid == 480 && b + WIN < 6) load_h(b + WIN);
      __syncwarp();
      mma(acc, 0, b);
    };
    auto finish = [&](float (&acc)[32], int b) {
      epi(acc, 0, b);
      __syncwarp();
      const int r = b * 64 + w * 16;
      if (lane == 0 && r < nloc) { proxy_fence(); tma_store(tmb + TM_Q, 0, node0 + r, A_QS + r * 128); }
      __syncwarp();
    };
#pragma unroll 1
    for (int b = 0; b < 6; b++) {
      begin(a0, b);
      if (w == 0 && b == 5) STAMP(17);
      wg_wait0(); fence_regs(a0);
      if (b == 5) bar_arrive(7, NT);
      finish(a0, b);
    }
    if (w == 0) STAMP(18);
    if (lane == 0) {
      bulk_commit();
      asm volatile("cp.async.bulk.wait_group 0;" ::: "memory");
      asm volatile("red.relaxed.gpu.global.add.u32 [%0], 1;" :: "l"(p.s->cnt) : "memory");
      if (w == 0) STAMP(19);
      const uint32_t nbe = (p.E / G) & ~15u;
#pragma unroll 1
      for (int i = w; i < PFA && w < 3; i += 3)
        if (nbe) asm volatile("cp.async.bulk.prefetch.L2.global [%0], %1;" :: "l"((const char*)p.ea + (size_t)(i * G + cta) * nbe), "r"(nbe) : "memory");
    }
    __syncwarp();
    ep++; tgb = (ep % 7 + 1) << 29;
  } else {
#pragma unroll
    for (int k = 0; k < 9; k++) if (k < 8 || tid < (G + 1) * 24 - 8 * NX) sts128(A_SA + (tid + k * NX) * 16, 0, 0, 0, 0);
    if (tid < (A_CNT - A_MISC) / 16) sts128(A_MISC + tid * 16, 0, tid == 0 ? 16 : 0, 0, 0);
    const uint32_t acnt = A_CNT + ((tid + cta * p.NPC) & 511) * 4;
    sts32(acnt, A_TAB + tid * (CAP * 2));
    if (tid < 32) sts32(A_CNT + 2048 + tid * 4, A_TAB + 385 * (CAP * 2));
    ep++; tgb = (ep % 7 + 1) << 29;
    const uint32_t tga = (ep % 127 + 1) * 0x02000200u, tgh = tga & 0xFFFF0000u;
    {
#pragma unroll
      for (int k = 0; k < 3; k++) { const uint32_t i = tid + k * NX, hw = ((i >> 3) & 31) - (i & 7) * 4; sts32p(A_SA + i * 16 + hw * 4, tgh + (i & 7) * 16 + hw * 4 + 4, hw < 4 && i < (G + 1) * 8); }
    }
    __syncthreads();
    STAMP(23);
    uint32_t d[16], oo[16], xx[16], lc[16], mxx = 0;
#pragma unroll
    for (int c = 0; c < 4; c++) {
      mbar_wait(BAR_C + c * 8, 0);
      if (c == 3) STAMP(1);
      lds128(d + 4 * c, a_dst(c) + tid * 16);
#pragma unroll
      for (int k = 4 * c; k < 4 * c + 4; k++) {
        if (tid * 16 + c * CH >= nb) d[k] = G * p.NPC;
        const uint32_t j = __umulhi(d[k], p.magic);
        xx[k] = atoms_add(A_SA + (j * 128 | ((j * 4) & 0x7C)), 258);
        oo[k] = j * 128;
      }
    }
#pragma unroll
    for (int k = 0; k < 16; k++) { oo[k] |= xx[k] & 0x7E; mxx = max(mxx, xx[k]); }
    if (mxx > tgh + 15900) {
#pragma unroll
      for (int k = 0; k < 16; k++) if (xx[k] > tgh + 15900) oo[k] = G * 128 + 64 + lane * 2;
    }
#pragma unroll
    for (int k = 0; k < 16; k++) sts16(A_SA + oo[k], (d[k] & 511) | tga);
    if (wid == 0) { bar_sync(1, NX); if (lane == 0) { proxy_fence(); tma_store_x(tmb + TM_XA, cta * 64, A_SA); bulk_commit(); } __syncwarp(); } else bar_arrive(1, NX);
    STAMP(2);
    const uint32_t eb = tgb + (tid << 18);
#pragma unroll
    for (int c = 0; c < 4; c++) {
      mbar_wait(BAR_C + 32 + c * 8, 0);
      if (wid == 0 && c == 3) STAMP(21);
      lds128(lc + 4 * c, A_SRC + c * CH + tid * 16);
#pragma unroll
      for (int k = 4 * c; k < 4 * c + 4; k++) { lc[k] += eb + ((c * NX * 4 + (k & 3)) << 16); sts32(A_SB + oo[k] * 2, lc[k]); }
    }
    bar_sync(2, NX);
    if (tid == 0) { proxy_fence(); tma_store_x(tmb + TM_XB, cta * 64, A_SB); bulk_commit(); p.s->ep[cta * 32] = ep; }
    __syncwarp();
    STAMP(3);
    if (mxx > tgh + 15900) {
#pragma unroll
      for (int k = 0; k < 16; k++) {
        const uint32_t j = __umulhi(d[k], p.magic), r = (xx[k] - tgh) / 258 - 62;
        if (r < 31 && j < G)
          asm volatile("st.relaxed.gpu.global.v2.u32 [%0], {%1, %2};" :: "l"(p.s->xe + (j * G + cta) * 32 + r), "r"(lc[k]), "r"((d[k] & 511) | (ep << 9)) : "memory");
      }
    }
    __syncwarp();
    uint32_t pk[11];
    const uint32_t rot = (lane + cta) & 31;
    const char* xa = (const char*)(p.s->xa + (cta * G + wid) * 8) + rot * 4;
    auto poll_a = [&]() {
#pragma unroll
      for (int k = 0; k < 11; k++) pk[k] = ldg_poll(xa + k * (12 * 128));
    };
#pragma unroll
    for (int k = 0; k < 7; k++) if (k < 6 || tid < 385 * CAP / 8 - 6 * NX) sts128(A_TAB + (tid + k * NX) * 16, 0, 0, 0, 0);
    if (PDELAY) __nanosleep(PDELAY);
    poll_a();
    bar_sync(3, NX);
    int spin = 0;
    STAMP(12);
    const uint32_t dum = (512 + lane) * 0x10001u, h0 = (cta & 31) * 4 + 4, h1 = h0 + 62 * 258;
    auto copy_b = [&]() {
      const uint32_t j = wid + 12 * (lane >> 4);
      const char* xb = (const char*)(p.s->xb + (cta * G + j) * 16 + (lane & 15));
#pragma unroll
      for (int k = 0; k < 6; k++) if (k < 5 || lane < 16)
      { if (XPOL & 2) asm volatile("cp.async.cg.shared.global.L2::cache_hint [%0], [%1], 16, %2;" :: "r"(A_IN + j * FS + 128 + (lane & 15) * 16 + k * 24 * FS), "l"(xb + k * (24 * 256)), "l"(pol_first()) : "memory");
        else asm volatile("cp.async.cg.shared.global [%0], [%1], 16;" :: "r"(A_IN + j * FS + 128 + (lane & 15) * 16 + k * 24 * FS), "l"(xb + k * (24 * 256)) : "memory"); }
    };
    uint32_t xs = ~0u; uint2 xv;
    for (;;) {
      uint32_t mh = 0, s0 = 0, s1 = 0;
#pragma unroll
      for (int k = 0; k < 11; k++) { const uint32_t y = pk[k] ^ tgh; mh = max(mh, y); s0 += min(y, h1); s1 += __vminu2(pk[k] ^ tga, dum) & 0x02000200u; }
      mh = __shfl_sync(~0u, mh, 0);
      s0 = __reduce_add_sync(~0u, lane ? (((s1 >> 9) & 15) + (s1 >> 25)) * 258 : s0);
      if (mh < 0x2000000 && s0 == 11 * h1) {
        if (mh > h1) {
          uint32_t base = 0;
#pragma unroll
          for (int k = 0; k < 11; k++) {
            const uint32_t c = (max(__shfl_sync(~0u, pk[k], 0) ^ tgh, h1) - h1) / 258;
            if (lane - base < c) xs = (wid + 12 * k) * 32 + lane - base;
            base += c;
          }
          if (base > 31) { sts32(A_MISC, 1); xs = ~0u; }
          if (xs != ~0u) xv = ldg_poll2(p.s->xe + cta * G * 32 + xs);
        }
        break;
      }
      if (++spin > 2000000) __trap();
      poll_a();
    }
    STAMP(14);
    uint32_t r0[11], r1[11];
#pragma unroll
    for (int k = 0; k < 11; k++) {
      pk[k] = __vminu2(lane ? pk[k] ^ tga : ~0u, dum);
      r0[k] = atoms_add(A_CNT + (pk[k] & 0xFFFF) * 4, 2);
      r1[k] = atoms_add(A_CNT + (pk[k] >> 16) * 4, 2);
    }
    const uint32_t t0 = wid * FS + 128 + rot * 8;
#pragma unroll
    for (int k = 0; k < 11; k++) { sts16(min(r0[k], A_IN - 2), t0 + 12 * k * FS); sts16(min(r1[k], A_IN - 2), t0 + 12 * k * FS + 4); }
    if (tid == 0) { asm volatile("cp.async.bulk.wait_group.read 0;" ::: "memory"); mbar_arrive(BAR_X); }
    __syncwarp();
    mbar_wait(BAR_X, 0);
    copy_b();
    STAMP(4);
    if (xs != ~0u) {
      while (((xv.x ^ tgb) >> 29) | ((xv.y >> 9) ^ (ep & 0x7FFFFF))) { xv = ldg_poll2(p.s->xe + cta * G * 32 + xs); if (++spin > 2000000) __trap(); }
      const uint32_t t = (xs >> 5) * FS + 4 + (xs & 31) * 4;
      sts16(min(atoms_add(A_CNT + (xv.y & 511) * 4, 2), A_IN - 2), t);
      sts32(A_IN + t, xv.x);
    }
    __syncwarp();
    bar_sync(4, NX);
    STAMP(5);
    {
      const uint32_t dg = (lds32(acnt) - (A_TAB + tid * (CAP * 2))) >> 1;
      const uint32_t dr = atoms_add(A_DH + min(dg, 63u) * 4, 1);
      bar_sync(5, NX);
      uint32_t hb, ha; lds64(hb, ha, A_DH + (62 - 2 * lane) * 4);
      uint32_t inc = ha + hb;
#pragma unroll
      for (int o = 1; o < 32; o <<= 1) { const uint32_t y = __shfl_up_sync(~0u, inc, o); if (lane >= o) inc += y; }
      const uint32_t idx = 63 - min(dg, 63u);
      const uint32_t e2 = __shfl_sync(~0u, (inc - hb) | ((inc - hb - ha) << 16), idx >> 1);
      const uint32_t pos = ((idx & 1) ? (e2 & 0xFFFF) : (e2 >> 16)) + dr;
      sts16(A_ROWS + pos * 2, tid);
      if (!(pos & 7)) sts32(A_LEN + (pos >> 1), max(1u, (dg + 1) >> 1));
      if (dg > CAP) sts32(A_MISC, 1);
    }
    STAMP(6);
    bar_sync(7, NT);
    { const int blk = (wid >> 2) * 2;
      mma(a0, 1, blk); mma(a1, 1, blk + 1);
      wg_wait0(); fence_regs(a0); fence_regs(a1);
      bar_sync(8 + (wid >> 2), 128);
      epi(a0, 1, blk); epi(a1, 1, blk + 1);
      const uint32_t pm = amax_warp(*(const uint32_t*)&mx & 0x7FFF7FFFu);
      if (pm > 0x7000 || (pm < 0x1400 && blk * 64 + (w + 1) * 16 <= min(p.NPC, p.N - cta * p.NPC))) sts32(A_MISC, 1);
    }
    STAMP(15);
    if (tid == 0) sts32(A_IN, 0xFFFF);
    for (;;) {
      asm volatile("cp.async.wait_all;" ::: "memory");
      __syncwarp();
      uint32_t bad = 0;
#pragma unroll
      for (int k = 0; k < 11; k++) {
        uint32_t x, y; lds64(x, y, A_IN + t0 + 12 * k * FS);
        bad |= (__byte_perm(x, y, 0x7632) ^ (tgb | (tgb >> 16))) & ((pk[k] | 0x20002000u) - 0x02000200u) * 8;
      }
      if (!__any_sync(~0u, bad & 0xE000E000u)) break;
      if (++spin > 2000000) __trap();
      copy_b();
    }
    STAMP(7);
  }
  uint32_t W3[16], PB[16], WX[8];
#pragma unroll
  for (int k = 0; k < 4; k++) ldsm4t(W3[4 * k], W3[4 * k + 1], W3[4 * k + 2], W3[4 * k + 3], A_W3 + (lane & 15) * 128 + ((((lane >> 4) + 2 * k) ^ (lane & 7)) << 4));
#pragma unroll
  for (int j = 0; j < 8; j++) WX[j] = lds32(A_WD + 128 + j * 16 + q * 4);
  if (tid == 480) {
    uint32_t c; int spin = 0;
    do { asm volatile("ld.acquire.gpu.global.u32 %0, [%1];" : "=r"(c) : "l"(p.s->cnt) : "memory"); if (++spin > 20000000) __trap(); } while ((int)(c - ep * (4 * G)) < 0);
    mbar_arrive(BAR_Q);
    STAMP(20);
  }
  __syncwarp();
  if (wid < 15) { bar_sync(11, NT - 32); if (wid == 14) bar_arrive(12, 64); } else bar_sync(12, 64);
  STAMP(13);
  if (lds32(A_MISC)) { __syncthreads(); slow_path(p); return; }

  {
    uint32_t MS[8], acc[16], m[16], A1[4], A2[4], OP, TA, D = 0, U = 0, tt, rec;
    const uint32_t ring = A_RING + wid * 5120;
    const int oc = lane >> 3;
    const int r7 = lane & 7, ro = r7 >> 1, ri = 2 * (oc & 1) + (r7 & 1);
    uint64_t qp0 = (uint64_t)p.s->q + ((r7 ^ (2 * oc)) << 4), qp1 = qp0 ^ 16, epp = (uint64_t)p.ea + (((lane ^ oc) & 1) << 4) - (tgb >> 11);
    uint32_t dq = ring + oc * 512 + r7 * 16, de = ring + 2048 + ((lane * 16) ^ ((oc >> 1) * 64));
    uint32_t rq = ring + (4 * ro + ri) * 128 + (((oc >> 1) ^ r7) << 4), re = ring + 2048 + ro * 128 + ((ri ^ (2 * (ro >> 1))) << 5) + ((((oc >> 1) ^ ro) & 1) << 4);
    A2[0] = (g8 >> 1) == q ? ((g8 & 1) ? 0x3C000000u : 0x3C00u) : 0;
    A2[0] += lds32(A_MISC); A2[1] = A2[0] + lds32(A_MISC);
    asm volatile("" : "+l"(qp0), "+l"(qp1), "+l"(epp), "+r"(dq), "+r"(de), "+r"(rq), "+r"(re));
    uint64_t pol; asm("createpolicy.fractional.L2::" EPOL ".b64 %0, 1.0;" : "=l"(pol));
    uint32_t mk, fq = wid;
    auto lane_id = []() { uint32_t l; asm volatile("mov.u32 %0, %%laneid;" : "=r"(l)); return l; };
    auto lset = [&](uint32_t id) { const uint32_t l = lane_id();
      TA = A_TAB + (id < 48 ? lds16(A_ROWS + id * 16 + (l >> 3) * 4 + (l & 2)) : 384) * (CAP * 2) + ((l >> 1) & 2); };
    auto lswitch = [&]() {
      const uint32_t id = __shfl_sync(~0u, atoms_incp(A_MISC + 4, lane_id() == 0), 0);
      lset(id);
      if (id < 48) { fq |= id << (6 + 6 * __popc(mk & 6)); mk |= 8u << __shfl_sync(~0u, lds32(A_LEN + id * 4), 0); }
      if ((id == HPF || id == 63) && lane_id() == 0) tail_loads(p, tmb, id);
      __syncwarp();
    };
    auto pswitch = [&]() {
      const uint32_t l = lane_id(), nd = lds16(A_ROWS + (fq & 63) * 16 + (l & 7) * 2);
      const uint32_t a = ((l & 8) ? A_WD2 + (l & 7) * 144 : A_PT + nd * 128 + ((nd & 7) << 4)) ^ (l & 16);
#pragma unroll
      for (int k = 0; k < 4; k++) ldsm4t(PB[4 * k], PB[4 * k + 1], PB[4 * k + 2], PB[4 * k + 3], a ^ (k << 5));
      OP = lds16(A_POSH + __shfl_sync(~0u, nd, l >> 2) * 8 + (l & 3) * 2) * 0x10001;
    };
    auto mswitch = [&]() {
      const uint32_t l = lane_id(), nd = lds16(A_ROWS + (fq & 63) * 16 + (l & 7) * 2), a = A_PT + nd * 128 + (((l >> 3) ^ (nd & 7)) << 4);
      uint32_t mx = U & 0x7FFF7FFFu;
#pragma unroll
      for (int j = 0; j < 8; j++) { mx = amax2(mx, MS[j]); MS[j] = h2b(MS[j]); }
      stsm4(a, MS[0], MS[1], MS[2], MS[3]); stsm4(a ^ 64, MS[4], MS[5], MS[6], MS[7]);
      const uint32_t pa = A_POSB + __shfl_sync(~0u, nd, l >> 2) * 6 + (l & 3) * 2;
      const float2 f = __half22float2(*(const __half2*)&U);
      sts16p(pa, pack_bf16(fmaf(f.x + f.y, __uint_as_float(lds32(A_MISC + 12)), bf_lo(lds16(pa))), 0.f), (l & 3) < 3);
      sts32p(A_MISC + 8, 1, ((mx + 0x04000400u) & 0x80008000u) != 0);
      U = 0;
#pragma unroll
      for (int j = 0; j < 8; j++) MS[j] = 0;
    };
    auto look = [&]() {
      asm volatile("ld.volatile.shared.u16 %0, [%1];" : "=r"(tt) : "r"(TA) : "memory"); TA += 4;
      asm volatile("ld.volatile.shared.u32 %0, [%1];" : "=r"(rec) : "r"(A_IN + tt) : "memory"); tt = __umulhi(tt, 11184811u) * p.EPC + (rec >> 16); rec &= 0xFFFF; };
    auto issue = [&](uint32_t st) {
#pragma unroll
      for (int i = 0; i < 4; i++)
        asm volatile("{.reg .b64 a; .reg .pred p, l; setp.eq.u32 p, %2, 0xFFFF; setp.ge.u32 l, %3, 8; mad.wide.u32 a, %2, 128, %1;\n @l cp.async.cg.shared.global [%0], [a], 16, p;}"
          :: "r"(dq + i * 128 + st), "l"((i & 1) ? qp1 : qp0), "r"(__shfl_sync(~0u, rec, 2 * i, 8)), "r"(mk) : "memory");
      asm volatile("{.reg .b64 a; .reg .pred p, l; setp.eq.u32 p, %3, 0xFFFF; setp.ge.u32 l, %4, 8; mad.wide.u32 a, %2, 32, %1;\n @l cp.async.cg.shared.global.L2::cache_hint [%0], [a], 16, p, %5;}"
        :: "r"(de + st), "l"(epp), "r"(tt), "r"(rec), "r"(mk), "l"(pol) : "memory");
      asm volatile("cp.async.commit_group;" ::: "memory");
    };
    auto cfin = [&]() {
      uint32_t c0_ = 0, c1_ = 0;
#pragma unroll
      for (int k = 0; k < 4; k++) hmma(c0_, c1_, m + 4 * k, WX[2 * k], WX[2 * k + 1]);
      U = hfma(__byte_perm(c0_, c1_, 0x5410), D, U);
    };
    auto step = [&](uint32_t st) {
      if (ORD == 0 && (mk & 9)) {
        if (mk & 1) { if (DEF) { cfin(); D = 0; } mswitch(); fq >>= 6; pswitch(); }
        if (mk & 8) lswitch();
      }
      asm volatile("cp.async.wait_group 1;" ::: "memory");
      __syncwarp();
      uint32_t E[4];
      ldsm4(E, re + st);
#pragma unroll
      for (int k = 0; k < 4; k++) ldsm4(acc + 4 * k, (rq ^ (k * 32)) + st);
      issue(st);
      if (ORD == 0) look();
      if (DEF && ORD != 2) cfin();
#pragma unroll
      for (int i = 0; i < 4; i++) A1[i] = b2h(E[i]);
      const uint32_t Sa = acc[0] + acc[2] * 4 + acc[4] * 16 + acc[6] * 64, Sb = acc[1] + acc[3] * 4 + acc[5] * 16 + acc[7] * 64;
      if (ORD && (mk & 9)) {
        if (mk & 1) { if (DEF && ORD == 2) { cfin(); D = 0; } mswitch(); fq >>= 6; pswitch(); }
        if (mk & 8) lswitch();
      }
      if (ORD) look();
      if (DEF && ORD == 2) cfin();
      mk >>= 1;
      D = hsub(OP, __byte_perm(Sa, Sb, 0x6420));
      const __half2 d = *(const __half2*)&D, x = __hmul2(d, d), y = __hmul2(__high2half2(d), __high2half2(d));
      A2[2] = *(const uint32_t*)&x; A2[3] = *(const uint32_t*)&y;
#pragma unroll
      for (int k = 0; k < 4; k++) {
#pragma unroll
        for (int j = 2 * k; j < 2 * k + 2; j++) { hmma(acc[2 * j], acc[2 * j + 1], A1, W3[2 * j], W3[2 * j + 1]); hmma(acc[2 * j], acc[2 * j + 1], A2, PB[2 * j], PB[2 * j + 1]); }
#pragma unroll
        for (int i = 0; i < 4; i++) { m[4 * k + i] = hsilu(acc[4 * k + i]); MS[2 * k + (i >> 1)] = hadd(MS[2 * k + (i >> 1)], m[4 * k + i]); }
      }
      if (!DEF) cfin();
    };
#pragma unroll
    for (int i = 0; i < 16; i++) m[i] = 0;
#pragma unroll
    for (int j = 0; j < 8; j++) MS[j] = 0;
    lset(wid); mk = 4u << __shfl_sync(~0u, lds32(A_LEN + wid * 4), 0); look();
    pswitch();
    mbar_wait(BAR_Q, 0);
    STAMP(8);
#pragma unroll 1
    for (int k = 0; k < 2; k++) { if (mk & 8) lswitch(); issue(k * 2560); look(); mk >>= 1; }
#pragma unroll 1
    for (uint32_t st = 0;; st ^= 2560) {
      if (UNR) { step(0); if (mk == 1) break; step(2560); } else step(st);
      if (mk == 1) break;
    }
    if (DEF) cfin();
    mswitch();
  }
  STAMP(9);
  {
    int tid, cta; asm volatile("mov.u32 %0, %%tid.x;" : "=r"(tid)); asm volatile("mov.u32 %0, %%ctaid.x;" : "=r"(cta));
    const int lane = tid & 31, wg = __shfl_sync(~0u, tid >> 7, 0), node0 = cta * p.NPC, nloc = max(0, min(p.NPC, p.N - node0));
    const uint32_t frag = (((tid >> 5) & 3) * 16 + (lane & 15)) * 128 + (((lane >> 4) ^ (lane & 7)) << 4);
    const int b2 = 4 + (wg >> 1), hf = wg & 1;
    const uint64_t dW = DHI | (A_TAB >> 4), dV = dW + hf * 4;
    const uint32_t h1 = A_IN + wg * 8192, h2 = A_IN + b2 * 8192;
    float acc[32], ac2[16];
    proxy_fence();
    mbar_wait(BAR_U, 0);
    { const uint64_t dH = DHI | (h1 >> 4), dG = DHI | (h2 >> 4);
      wg_fence();
      ss64<0>(acc, dH, dW); ss64<1>(acc, dH + 2, dW + 128); ss64<1>(acc, dH + 4, dW + 256); ss64<1>(acc, dH + 6, dW + 384);
      ss32<0>(ac2, dG, dV); ss32<1>(ac2, dG + 2, dV + 128); ss32<1>(ac2, dG + 4, dV + 256); ss32<1>(ac2, dG + 6, dV + 384);
      wg_commit(); wg_wait0(); fence_regs(acc); fence_regs(ac2); }
    __syncthreads();
    STAMP(10);
    if (lds32(A_MISC + 8)) { slow_path(p); return; }
    { const uint64_t dM = DHI | ((A_PT + wg * 8192) >> 4), dN = DHI | ((A_PT + b2 * 8192) >> 4);
      wg_fence();
      ss64<1>(acc, dM, dW + 512); ss64<1>(acc, dM + 2, dW + 640); ss64<1>(acc, dM + 4, dW + 768); ss64<1>(acc, dM + 6, dW + 896);
      wg_commit();
      for (int i = tid; i < nloc * 3; i += NT) p.out[(size_t)p.N * 64 + (size_t)node0 * 3 + i] = (uint16_t)lds16(A_POSB + i * 2);
      wg_wait0(); fence_regs(acc);
      wg_fence();
      ss32<1>(ac2, dN, dV + 512); ss32<1>(ac2, dN + 2, dV + 640); ss32<1>(ac2, dN + 4, dV + 768); ss32<1>(ac2, dN + 6, dV + 896);
      wg_commit(); }
    auto fin = [&](uint32_t x, float y0, float y1) { return badd(x, pack_bf16(silu(y0), silu(y1))); };
    auto put_block = [&](int blk, uint32_t src) {
      if (blk * 64 < nloc) tma_store((blk + 1) * 64 <= p.NPC ? tmb + TM_O : tmb + TM_O2, 0, node0 + blk * 64, src);
      bulk_commit();
    };
#pragma unroll
    for (int j = 0; j < 4; j++) {
      uint32_t x[4]; ldsm4(x, (h1 + frag) ^ (j << 5));
      stsm4((h1 + frag) ^ (j << 5), fin(x[0], acc[8 * j], acc[8 * j + 1]), fin(x[1], acc[8 * j + 2], acc[8 * j + 3]), fin(x[2], acc[8 * j + 4], acc[8 * j + 5]), fin(x[3], acc[8 * j + 6], acc[8 * j + 7]));
    }
    wg_wait0(); fence_regs(ac2);
    proxy_fence();
    bar_sync(6 + wg, 128);
    if ((tid & 127) == 0) put_block(wg, h1);
    __syncwarp();
#pragma unroll
    for (int j = 0; j < 2; j++) {
      const uint32_t a = (h2 + frag) ^ ((2 * hf + j) << 5);
      uint32_t x[4]; ldsm4(x, a);
      stsm4(a, fin(x[0], ac2[8 * j], ac2[8 * j + 1]), fin(x[1], ac2[8 * j + 2], ac2[8 * j + 3]), fin(x[2], ac2[8 * j + 4], ac2[8 * j + 5]), fin(x[3], ac2[8 * j + 6], ac2[8 * j + 7]));
    }
    proxy_fence();
    bar_sync(10 + (wg >> 1), 256);
    if ((tid & 127) == 0) {
      if (!hf) put_block(b2, h2);
      asm volatile("cp.async.bulk.wait_group.read 0;" ::: "memory");
    }
  }
  STAMP(11);
}

}

typedef CUresult (*EncodeFn)(CUtensorMap*, CUtensorMapDataType, cuuint32_t, void*, const cuuint64_t*, const cuuint64_t*, const cuuint32_t*, const cuuint32_t*,
                             CUtensorMapInterleave, CUtensorMapSwizzle, CUtensorMapL2promotion, CUtensorMapFloatOOBfill);

extern "C" void kernel_launch(void* const* d_in, const int* in_sizes, int n_in, void* d_out, int out_size) {
  Params p; Maps maps;
  p.h = (const uint16_t*)d_in[0]; p.pos = (const uint16_t*)d_in[1]; p.ea = (const uint16_t*)d_in[2];
  p.src = (const int*)d_in[3]; p.dst = (const int*)d_in[4];
  p.we = (const uint16_t*)d_in[5]; p.wx = (const uint16_t*)d_in[6]; p.wh = (const uint16_t*)d_in[7];
  p.out = (uint16_t*)d_out;
  p.N = in_sizes[0] / 64; p.E = in_sizes[3];
  p.NPC = (p.N + G - 1) / G;
  p.EPC = ((p.E + G * 4 - 1) / (G * 4)) * 4;
  p.magic = (uint32_t)((1ull << 32) / (uint64_t)p.NPC) + 1;
  uint64_t al = (uint64_t)d_out;
  for (int i = 0; i < 8; i++) if (i != 1) al |= (uint64_t)d_in[i];
  p.force_slow = (al & 31) || (p.E & 3) || p.NPC > 384 || p.NPC < 2 || p.EPC > 6144;
  cudaGetSymbolAddress((void**)&p.s, g_s);
  void* fn = nullptr; cudaDriverEntryPointQueryResult qr;
  cudaGetDriverEntryPoint("cuTensorMapEncodeTiled", &fn, cudaEnableDefault, &qr);
  auto mk = [&](CUtensorMap* tm, void* base, int rows, int box) {
    const cuuint64_t dim[2] = {64, (cuuint64_t)rows}, str[1] = {128}; const cuuint32_t bx[2] = {64, (cuuint32_t)box}, es[2] = {1, 1};
    ((EncodeFn)fn)(tm, CU_TENSOR_MAP_DATA_TYPE_BFLOAT16, 2, base, dim, str, bx, es, CU_TENSOR_MAP_INTERLEAVE_NONE, CU_TENSOR_MAP_SWIZZLE_128B,
                   CU_TENSOR_MAP_L2_PROMOTION_NONE, CU_TENSOR_MAP_FLOAT_OOB_FILL_NONE);
  };
  mk(&maps.m[TM_H / 128], d_in[0], p.N, 64); mk(&maps.m[TM_WE / 128], d_in[5], 145, 64); mk(&maps.m[TM_WH / 128], d_in[7], 128, 64);
  mk(&maps.m[TM_Q / 128], p.s->q, p.N, 16); mk(&maps.m[TM_O / 128], d_out, p.N, 64); mk(&maps.m[TM_O2 / 128], d_out, p.N, (p.NPC & 63) ? (p.NPC & 63) : 64);
  mk(&maps.m[TM_W3 / 128], d_in[5], 145, 16);
  for (int k = 0; k < 2; k++) {
    void* xp = k ? (void*)p.s->xb : (void*)p.s->xa;
    const cuuint64_t dim[2] = {(cuuint64_t)G * 64, (cuuint64_t)G}, str[1] = {(cuuint64_t)G * (128 << k)}; const cuuint32_t bx[2] = {64, G}, es[2] = {1, 1};
    ((EncodeFn)fn)(&maps.m[TM_XA / 128 + k], k ? CU_TENSOR_MAP_DATA_TYPE_UINT32 : CU_TENSOR_MAP_DATA_TYPE_UINT16, 2, xp, dim, str, bx, es, CU_TENSOR_MAP_INTERLEAVE_NONE,
                   CU_TENSOR_MAP_SWIZZLE_NONE, CU_TENSOR_MAP_L2_PROMOTION_NONE, CU_TENSOR_MAP_FLOAT_OOB_FILL_NONE);
  }
  cudaFuncSetAttribute(egnn_kernel, cudaFuncAttributeMaxDynamicSharedMemorySize, SMEM);
  egnn_kernel<<<G, NT, SMEM>>>(p, maps);
}
```

```cpp
#include <cuda_runtime.h>
#include <cuda_bf16.h>
#include <cuda_fp16.h>
#include <cuda.h>
#include <stdint.h>

#define PFA 4
#define HPF 99
#define CHK 8192
#define EPOL "evict_first"
#define XPOL 2
#define ORD 0
#define WIN 6
#define RF 3
#define PFT 400
#define QHOLD 1
#define PSW 1
#define TLBW 0
#define BL 0
#define CBH 1
#define UNR 1
#define DEF 2
namespace {

constexpr int G = 132;
constexpr int NT = 512;
constexpr int CAP = 48;
constexpr int FS = 384;
constexpr uint32_t sb = 1024;

constexpr uint32_t A_RING = sb;
constexpr uint32_t A_PT = A_RING + 16 * 5120;
constexpr uint32_t A_W3 = A_PT + 49152;
constexpr uint32_t A_TAB = A_W3 + 2048;
constexpr uint32_t A_IN = A_TAB + 37888;
constexpr uint32_t A_WD = A_IN + G * FS + 512;
constexpr uint32_t A_WD2 = A_WD + 256;
constexpr uint32_t A_BAR = A_WD2 + 1024;
constexpr uint32_t A_MISC = A_BAR + 160;
constexpr uint32_t A_DH = A_MISC + 16;
constexpr uint32_t A_CNT = A_DH + 256;
constexpr uint32_t A_POSH = A_CNT + 2176;
constexpr uint32_t A_POSB = A_POSH + 3072;
constexpr uint32_t A_ROWS = A_POSB + 2304;
constexpr uint32_t A_LEN = A_ROWS + 768;
constexpr uint32_t A_END = A_LEN + 192;
constexpr int SMEM = A_END - sb;
static_assert(SMEM <= 232448 && A_TAB % 1024 == 0 && A_IN % 1024 == 0 && A_PT % 1024 == 0 && A_WD2 % 128 == 0, "smem");
constexpr int NX = 384, CH = NX * 16;
constexpr uint32_t A_QS = A_RING, A_W = A_QS + 49152, A_SA = A_IN, A_SB = A_SA + (G + 1) * 128, A_SRC = A_TAB;
__host__ __device__ constexpr uint32_t a_dst(int k) { return k < 2 ? A_W + 16384 + k * CH : A_SRC + (k + 2) * CH; }
static_assert(a_dst(1) + CH <= A_PT && a_dst(3) + CH <= A_IN && A_SB + (G + 1) * 256 <= A_WD, "staging");
constexpr uint32_t BAR_C = A_BAR, BAR_T = BAR_C + 64, BAR_W = A_BAR + 112, BAR_U = A_BAR + 120, BAR_Q = A_BAR + 128, BAR_X = A_BAR + 136, BAR_A = A_BAR + 144;

#define ABL 0
#define JSV 12
#define ESZ ""
#define VAR 0
#define STAT 1
#define PFB 0
#define PFR 3
#define EFR "1.0"
#define EKEEP 0
#define NREPV 8
#define PFD 0
#define EH 1
constexpr int NREP = NREPV;
struct Scratch {
  uint4 q[(G * 384 + 64) * 8];
  uint4 x[G * G * 24];
  uint2 xe[G * G * 32];
  uint32_t ep[G * 32];
  uint32_t cnt[NREP * 32];
};
__device__ __align__(256) Scratch g_s;
#define STAMP(k)

struct Maps { CUtensorMap m[9]; };
constexpr int TM_H = 0, TM_WE = 128, TM_WH = 256, TM_Q = 384, TM_O = 512, TM_O2 = 640, TM_XA = 768, TM_XB = 896, TM_W3 = 1024;
struct Params {
  const int* dst; const int* src; int E, EPC, force_slow, NPC; Scratch* s; int N; uint32_t magic;
  const uint16_t* h; const uint16_t* pos; const uint16_t* ea; const uint16_t* we; const uint16_t* wx; const uint16_t* wh; uint16_t* out;
  uint32_t sched[16];
};

#define R32(d) "+f"(d[0]),"+f"(d[1]),"+f"(d[2]),"+f"(d[3]),"+f"(d[4]),"+f"(d[5]),"+f"(d[6]),"+f"(d[7]),"+f"(d[8]),"+f"(d[9]),"+f"(d[10]),"+f"(d[11]),"+f"(d[12]),"+f"(d[13]),"+f"(d[14]),"+f"(d[15]),"+f"(d[16]),"+f"(d[17]),"+f"(d[18]),"+f"(d[19]),"+f"(d[20]),"+f"(d[21]),"+f"(d[22]),"+f"(d[23]),"+f"(d[24]),"+f"(d[25]),"+f"(d[26]),"+f"(d[27]),"+f"(d[28]),"+f"(d[29]),"+f"(d[30]),"+f"(d[31])
#define S32 "{%0,%1,%2,%3,%4,%5,%6,%7,%8,%9,%10,%11,%12,%13,%14,%15,%16,%17,%18,%19,%20,%21,%22,%23,%24,%25,%26,%27,%28,%29,%30,%31}"
#define R16(d) "+f"(d[0]),"+f"(d[1]),"+f"(d[2]),"+f"(d[3]),"+f"(d[4]),"+f"(d[5]),"+f"(d[6]),"+f"(d[7]),"+f"(d[8]),"+f"(d[9]),"+f"(d[10]),"+f"(d[11]),"+f"(d[12]),"+f"(d[13]),"+f"(d[14]),"+f"(d[15])
#define S16 "{%0,%1,%2,%3,%4,%5,%6,%7,%8,%9,%10,%11,%12,%13,%14,%15}"
#define DI __device__ __forceinline__

constexpr uint64_t DHI = (64ull << 32) | (1ull << 62);
template<int SD> DI void ss64(float (&d)[32], uint64_t da, uint64_t db) {
  asm volatile("wgmma.mma_async.sync.aligned.m64n64k16.f32.bf16.bf16 " S32 ", %32, %33, %34, 1, 1, 0, 1;" : R32(d) : "l"(da), "l"(db), "n"(SD)); }
template<int SD> DI void ss32(float (&d)[16], uint64_t da, uint64_t db) {
  asm volatile("wgmma.mma_async.sync.aligned.m64n32k16.f32.bf16.bf16 " S16 ", %16, %17, %18, 1, 1, 0, 1;" : R16(d) : "l"(da), "l"(db), "n"(SD)); }
DI void wg_fence() { asm volatile("wgmma.fence.sync.aligned;" ::: "memory"); }
DI void wg_commit() { asm volatile("wgmma.commit_group.sync.aligned;" ::: "memory"); }
DI void wg_wait0() { asm volatile("wgmma.wait_group.sync.aligned 0;" ::: "memory"); }
DI void fence_regs(float (&d)[32]) { asm volatile("" : R32(d) :: "memory"); }
DI void fence_regs(float (&d)[16]) { asm volatile("" : R16(d) :: "memory"); }
DI void proxy_fence() { asm volatile("fence.proxy.async.shared::cta;" ::: "memory"); }
DI void hmma(uint32_t& d0, uint32_t& d1, const uint32_t* a, uint32_t b0, uint32_t b1) {
  asm("mma.sync.aligned.m16n8k16.row.col.f16.f16.f16.f16 {%0,%1}, {%2,%3,%4,%5}, {%6,%7}, {%0,%1};" : "+r"(d0), "+r"(d1) : "r"(a[0]), "r"(a[1]), "r"(a[2]), "r"(a[3]), "r"(b0), "r"(b1)); }
DI uint64_t pol_first() { uint64_t r; asm("createpolicy.fractional.L2::evict_first.b64 %0, 1.0;" : "=l"(r)); return r; }
DI float tanh_ap(float x) { float y; asm("tanh.approx.f32 %0, %1;" : "=f"(y) : "f"(x)); return y; }
DI float silu(float x) { const float y = 0.5f * x; return fmaf(y, tanh_ap(y), y); }
DI uint32_t pack_bf16(float lo, float hi) { uint32_t r; asm("cvt.rn.bf16x2.f32 %0, %1, %2;" : "=r"(r) : "f"(hi), "f"(lo)); return r; }
DI uint32_t pack_f16(float lo, float hi) { uint32_t r; asm("cvt.rn.f16x2.f32 %0, %1, %2;" : "=r"(r) : "f"(hi), "f"(lo)); return r; }
DI float bf_lo(uint32_t v) { return __uint_as_float(v << 16); }
DI float bf_hi(uint32_t v) { return __uint_as_float(v & 0xFFFF0000u); }
DI uint32_t b2h(uint32_t v) { return pack_f16(bf_lo(v), bf_hi(v)); }
DI uint32_t h2b(uint32_t v) { const float2 f = __half22float2(*(const __half2*)&v); return pack_bf16(f.x, f.y); }
DI uint32_t hadd(uint32_t a, uint32_t b) { uint32_t r; asm("add.rn.f16x2 %0, %1, %2;" : "=r"(r) : "r"(a), "r"(b)); return r; }
DI uint32_t hsub(uint32_t a, uint32_t b) { uint32_t r; asm("sub.rn.f16x2 %0, %1, %2;" : "=r"(r) : "r"(a), "r"(b)); return r; }
DI uint32_t hfma(uint32_t a, uint32_t b, uint32_t c) { uint32_t r; asm("fma.rn.f16x2 %0, %1, %2, %3;" : "=r"(r) : "r"(a), "r"(b), "r"(c)); return r; }
DI uint32_t hsilu(uint32_t y) { uint32_t t; asm("tanh.approx.f16x2 %0, %1;" : "=r"(t) : "r"(y)); return hfma(y, t, y); }
DI uint32_t badd(uint32_t a, uint32_t b) { uint32_t r; asm("add.rn.bf16x2 %0, %1, %2;" : "=r"(r) : "r"(a), "r"(b)); return r; }
DI uint32_t bhalf(uint32_t v) { uint32_t r; asm("mul.rn.bf16x2 %0, %1, %2;" : "=r"(r) : "r"(v), "r"(0x3F003F00u)); return r; }
DI uint32_t amax2(uint32_t mx, uint32_t v) { return __vmaxu2(mx, v & 0x7FFF7FFFu); }
DI uint32_t amax_warp(uint32_t mx) { return __reduce_max_sync(~0u, max(mx & 0xFFFF, mx >> 16)); }
DI void mbar_wait(uint32_t bar, uint32_t parity) {
  asm volatile("{.reg .pred p; .reg .u32 c; mov.u32 c, 0;\n"
    "LW_%=: mbarrier.try_wait.parity.shared::cta.b64 p, [%0], %1;\n"
    "@p bra.uni LD_%=;\n add.u32 c, c, 1; setp.lt.u32 p, c, 20000000;\n @p bra.uni LW_%=;\n LD_%=:}" :: "r"(bar), "r"(parity) : "memory");
}
DI void mbar_arrive(uint32_t bar) { asm volatile("mbarrier.arrive.shared::cta.b64 _, [%0];" :: "r"(bar) : "memory"); }
DI void bar_sync(int id, int n) { asm volatile("bar.sync %0, %1;" :: "r"(id), "r"(n) : "memory"); }
DI void bar_arrive(int id, int n) { asm volatile("bar.arrive %0, %1;" :: "r"(id), "r"(n) : "memory"); }
DI void sts128(uint32_t a, uint32_t x, uint32_t y, uint32_t z, uint32_t w) { asm volatile("st.shared.v4.u32 [%0], {%1,%2,%3,%4};" :: "r"(a), "r"(x), "r"(y), "r"(z), "r"(w) : "memory"); }
DI void sts64(uint32_t a, uint32_t x, uint32_t y) { asm volatile("st.shared.v2.u32 [%0], {%1,%2};" :: "r"(a), "r"(x), "r"(y) : "memory"); }
DI void sts32(uint32_t a, uint32_t x) { asm volatile("st.shared.u32 [%0], %1;" :: "r"(a), "r"(x) : "memory"); }
DI void sts16(uint32_t a, uint32_t x) { asm volatile("st.shared.u16 [%0], %1;" :: "r"(a), "h"((uint16_t)x) : "memory"); }
DI void sts32p(uint32_t a, uint32_t x, bool p) { asm volatile("{.reg .pred p; setp.ne.b32 p, %2, 0; @p st.shared.u32 [%0], %1;}" :: "r"(a), "r"(x), "r"((int)p) : "memory"); }
DI void sts16p(uint32_t a, uint32_t x, bool p) { asm volatile("{.reg .pred p; setp.ne.b32 p, %2, 0; @p st.shared.u16 [%0], %1;}" :: "r"(a), "h"((uint16_t)x), "r"((int)p) : "memory"); }
DI void lds128(uint32_t* v, uint32_t a) { asm volatile("ld.shared.v4.u32 {%0, %1, %2, %3}, [%4];" : "=r"(v[0]), "=r"(v[1]), "=r"(v[2]), "=r"(v[3]) : "r"(a) : "memory"); }
DI void lds64(uint32_t& x, uint32_t& y, uint32_t a) { asm volatile("ld.shared.v2.u32 {%0, %1}, [%2];" : "=r"(x), "=r"(y) : "r"(a) : "memory"); }
DI uint32_t lds32(uint32_t a) { uint32_t x; asm volatile("ld.shared.u32 %0, [%1];" : "=r"(x) : "r"(a) : "memory"); return x; }
DI uint32_t lds16(uint32_t a) { uint32_t x; asm volatile("ld.shared.u16 %0, [%1];" : "=r"(x) : "r"(a) : "memory"); return x; }
DI uint32_t atoms_add(uint32_t a, uint32_t v) { uint32_t r; asm volatile("atom.shared.add.u32 %0, [%1], %2;" : "=r"(r) : "r"(a), "r"(v) : "memory"); return r; }
DI uint32_t atoms_incp(uint32_t a, bool p) { uint32_t r = 0; asm volatile("{.reg .pred p; setp.ne.b32 p, %2, 0; @p atom.shared.add.u32 %0, [%1], 1;}" : "+r"(r) : "r"(a), "r"((int)p) : "memory"); return r; }
DI uint32_t ldg_poll(const void* a) { uint32_t x; asm volatile("ld.relaxed.gpu.global.u32 %0, [%1];" : "=r"(x) : "l"(a) : "memory"); return x; }
DI uint2 ldg_poll2(const void* a) { uint2 x; asm volatile("ld.relaxed.gpu.global.v2.u32 {%0, %1}, [%2];" : "=r"(x.x), "=r"(x.y) : "l"(a) : "memory"); return x; }
DI void bulk_load(uint32_t dst, const void* src, uint32_t bytes, uint32_t bar) {
  asm volatile("cp.async.bulk.shared::cluster.global.mbarrier::complete_tx::bytes.L2::cache_hint [%0], [%1], %2, [%3], %4;" :: "r"(dst), "l"(src), "r"(bytes), "r"(bar), "l"(pol_first()) : "memory"); }
DI void mbar_expect(uint32_t bar, uint32_t bytes) { asm volatile("mbarrier.arrive.expect_tx.shared::cta.b64 _, [%0], %1;" :: "r"(bar), "r"(bytes) : "memory"); }
DI void mbar_init(uint32_t bar, int n) { asm volatile("mbarrier.init.shared::cta.b64 [%0], %1;" :: "r"(bar), "r"(n) : "memory"); }
DI void tma_load(uint32_t dst, uint64_t tm, int row, uint32_t bar) {
  asm volatile("cp.async.bulk.tensor.2d.shared::cluster.global.mbarrier::complete_tx::bytes.L2::cache_hint [%0], [%1, {%3, %4}], [%2], %5;" :: "r"(dst), "l"(tm), "r"(bar), "r"(0), "r"(row), "l"(pol_first()) : "memory"); }
DI void tma_store(uint64_t tm, int col, int row, uint32_t src) {
  asm volatile("cp.async.bulk.tensor.2d.global.shared::cta.bulk_group [%0, {%2, %3}], [%1];" :: "l"(tm), "r"(src), "r"(col), "r"(row) : "memory"); }
DI void tma_store_x(uint64_t tm, int col, uint32_t src) {
  if (XPOL & 1) asm volatile("cp.async.bulk.tensor.2d.global.shared::cta.bulk_group.L2::cache_hint [%0, {%2, 0}], [%1], %3;" :: "l"(tm), "r"(src), "r"(col), "l"(pol_first()) : "memory");
  else tma_store(tm, col, 0, src); }
DI void bulk_commit() { asm volatile("cp.async.bulk.commit_group;" ::: "memory"); }
DI void stsm4(uint32_t a, uint32_t x, uint32_t y, uint32_t z, uint32_t w) { asm volatile("stmatrix.sync.aligned.m8n8.x4.shared.b16 [%0], {%1,%2,%3,%4};" :: "r"(a), "r"(x), "r"(y), "r"(z), "r"(w) : "memory"); }
DI void ldsm4(uint32_t* v, uint32_t a) { asm volatile("ldmatrix.sync.aligned.m8n8.x4.shared.b16 {%0,%1,%2,%3}, [%4];" : "=r"(v[0]), "=r"(v[1]), "=r"(v[2]), "=r"(v[3]) : "r"(a) : "memory"); }
DI void ldsm4t(uint32_t& x, uint32_t& y, uint32_t& z, uint32_t& w, uint32_t a) { asm volatile("ldmatrix.sync.aligned.m8n8.x4.trans.shared.b16 {%0,%1,%2,%3}, [%4];" : "=r"(x), "=r"(y), "=r"(z), "=r"(w) : "r"(a) : "memory"); }

__device__ __noinline__ void slow_path(const Params& p) {
  const int lane = threadIdx.x & 31, wid = threadIdx.x >> 5;
  const uint32_t ab = sb + wid * (24 * 528);
  const uint32_t* we = (const uint32_t*)p.we;
  const int nend = min(p.N, (blockIdx.x + 1) * p.NPC);
  auto rowmul = [&](uint32_t hv, const uint32_t* w, float& y0, float& y1) {
#pragma unroll 4
    for (int k = 0; k < 32; k++) {
      const uint32_t hk = __shfl_sync(~0u, hv, k), wa = __ldg(w + 2 * k * 32 + lane), wb = __ldg(w + (2 * k + 1) * 32 + lane);
      y0 = fmaf(bf_lo(hk), bf_lo(wa), fmaf(bf_hi(hk), bf_lo(wb), y0)); y1 = fmaf(bf_lo(hk), bf_hi(wa), fmaf(bf_hi(hk), bf_hi(wb), y1));
    }
  };
  auto act = [](float x) { return x / (1.f + __expf(-x)); };
  auto hrow = [&](int n) { return __ldg(p.h + (size_t)n * 64 + 2 * lane) | ((uint32_t)__ldg(p.h + (size_t)n * 64 + 2 * lane + 1) << 16); };
  const uint32_t wdv = __ldg(we + 128 * 32 + lane), wxv = __ldg((const uint32_t*)p.wx + lane);
  for (int nb = blockIdx.x * p.NPC + wid * 24; nb < nend; nb += 384) {
    const int cnt = min(24, nend - nb);
    for (int n = 0; n < cnt; n++) {
      float y0 = 0.f, y1 = 0.f; rowmul(hrow(nb + n), we, y0, y1);
      sts64(ab + n * 528 + lane * 8, 0, 0); sts64(ab + n * 528 + 256 + lane * 8, __float_as_uint(y0), __float_as_uint(y1));
      if (lane < 4) sts32(ab + n * 528 + 512 + lane * 4, 0);
    }
    __syncwarp();
    for (int base = 0; base < p.E; base += 32) {
      const uint32_t dl = base + lane < p.E ? (uint32_t)(__ldg(p.dst + base + lane) - nb) : 0xFFFFFFFFu;
      uint32_t mk = __ballot_sync(~0u, dl < (uint32_t)cnt);
      while (mk) {
        const int l = __ffs(mk) - 1; mk &= mk - 1;
        const int e = base + l, n = __shfl_sync(~0u, dl, l), s = __ldg(p.src + e);
        const uint32_t a = ab + n * 528;
        float df = 0.f;
        if (lane < 3) df = bf_lo(pack_bf16(bf_lo(__ldg(p.pos + (size_t)(nb + n) * 3 + lane)) - bf_lo(__ldg(p.pos + (size_t)s * 3 + lane)), 0.f));
        float d2 = df * df; d2 += __shfl_xor_sync(~0u, d2, 1); d2 += __shfl_xor_sync(~0u, d2, 2); d2 = __shfl_sync(~0u, d2, 0);
        uint32_t x0, x1; lds64(x0, x1, a + 256 + lane * 8);
        float y0 = fmaf(d2, bf_lo(wdv), __uint_as_float(x0)), y1 = fmaf(d2, bf_hi(wdv), __uint_as_float(x1));
        rowmul(hrow(s), we + 64 * 32, y0, y1);
        for (int k = 0; k < 16; k++) { const float ev = bf_lo(__ldg(p.ea + (size_t)e * 16 + k)); const uint32_t w = __ldg(we + (129 + k) * 32 + lane); y0 = fmaf(ev, bf_lo(w), y0); y1 = fmaf(ev, bf_hi(w), y1); }
        y0 = act(y0); y1 = act(y1);
        float c = y0 * bf_lo(wxv) + y1 * bf_hi(wxv);
#pragma unroll
        for (int o = 16; o; o >>= 1) c += __shfl_xor_sync(~0u, c, o);
        lds64(x0, x1, a + lane * 8);
        sts64(a + lane * 8, __float_as_uint(__uint_as_float(x0) + y0), __float_as_uint(__uint_as_float(x1) + y1));
        if (lane < 3) sts32(a + 512 + lane * 4, __float_as_uint(fmaf(c, df, __uint_as_float(lds32(a + 512 + lane * 4)))));
      }
    }
    __syncwarp();
    for (int n = 0; n < cnt; n++) {
      const uint32_t hv = hrow(nb + n); uint32_t x0, x1; lds64(x0, x1, ab + n * 528 + lane * 8);
      float y0 = 0.f, y1 = 0.f; rowmul(hv, (const uint32_t*)p.wh, y0, y1); rowmul(pack_bf16(__uint_as_float(x0), __uint_as_float(x1)), (const uint32_t*)p.wh + 64 * 32, y0, y1);
      const uint32_t o = badd(hv, pack_bf16(act(y0), act(y1)));
      p.out[(size_t)(nb + n) * 64 + 2 * lane] = (uint16_t)o; p.out[(size_t)(nb + n) * 64 + 2 * lane + 1] = (uint16_t)(o >> 16);
      if (lane < 3) p.out[(size_t)p.N * 64 + (size_t)(nb + n) * 3 + lane] = (uint16_t)pack_bf16(bf_lo(__ldg(p.pos + (size_t)(nb + n) * 3 + lane)) + __uint_as_float(lds32(ab + n * 528 + 512 + lane * 4)), 0.f);
    }
    __syncwarp();
  }
}

DI void prefetch_e(const Params& p, int i) {
  int cta; asm volatile("mov.u32 %0, %%ctaid.x;" : "=r"(cta));
  const uint32_t nbe = (p.E / G) & ~15u;
  if (nbe) asm volatile("cp.async.bulk.prefetch.L2.global [%0], %1;" :: "l"((const char*)p.ea + (size_t)(i * G + cta) * nbe), "r"(nbe) : "memory");
}
DI void tail_loads(const Params& p, uint64_t tmb, uint32_t id) {
  int cta; asm volatile("mov.u32 %0, %%ctaid.x;" : "=r"(cta));
  const int node0 = cta * p.NPC, nloc = min(p.NPC, p.N - node0);
  if (id != 63) { if (nloc > 0) asm volatile("cp.async.bulk.prefetch.L2.global [%0], %1;" :: "l"(p.h + (size_t)node0 * 64), "r"(nloc * 128) : "memory"); }
  else {
    proxy_fence();
    mbar_expect(BAR_U, 65536);
#pragma unroll 1
    for (int b = 0; b < 8; b++) tma_load(b < 2 ? A_TAB + b * 8192 : A_IN + (b - 2) * 8192, tmb + (b < 2 ? TM_WH : TM_H), b < 2 ? b * 64 : node0 + (b - 2) * 64, BAR_U);
  }
}

__global__ void __launch_bounds__(NT, 1) egnn_kernel(const __grid_constant__ Params p, const __grid_constant__ Maps maps) {
  extern __shared__ __align__(1024) unsigned char smraw[];
  const int tid = threadIdx.x, cta = blockIdx.x;
  const int e0 = cta * p.EPC, nb = max(0, min(p.EPC, p.E - e0)) * 4;
  STAMP(0);
  auto load_idx = [&](int c) {
    const int o = (c & 3) * CH, n = max(0, min(CH, nb - o));
    mbar_expect(BAR_C + c * 8, n);
    if (n) bulk_load(c < 4 ? a_dst(c) : A_SRC + o, (const char*)((c < 4 ? p.dst : p.src) + e0) + o, n, BAR_C + c * 8);
  };
  if (tid == 480 && !p.force_slow) {
#pragma unroll
    for (int c = 0; c < 4; c++) mbar_init(BAR_C + c * 8, 1);
    asm volatile("fence.mbarrier_init.release.cluster;" ::: "memory");
#pragma unroll
    for (int c = 0; c < 4; c++) load_idx(c);
  }
  if ((uint32_t)__cvta_generic_to_shared(smraw) != sb) return;
  if (p.force_slow) { slow_path(p); return; }
  uint32_t ep = ldg_poll(p.s->ep + cta * 32), tgb;
  const uint64_t tmb = (uint64_t)&maps;
  const int lane = tid & 31, wid = __shfl_sync(~0u, tid >> 5, 0), g8 = lane >> 2, q = lane & 3;
  if (wid >= 12) {
    if (tid == 480 || tid == 448) {
#pragma unroll
      for (int c = 0; c < 10; c++) if (tid == 480 || c < 5) mbar_init(BAR_C + (tid == 480 ? 32 : 112) + c * 8, 1);
      asm volatile("fence.mbarrier_init.release.cluster;" ::: "memory");
    }
    if (tid - 416 < 9u) asm volatile("prefetch.tensormap [%0];" :: "l"(tmb + (tid - 416) * 128));
    __syncwarp();
    if (wid == 15) bar_arrive(7, NT); else bar_sync(7, NT);
    if (tid == 480) {
#pragma unroll 1
      for (int c = 4; c < 14; c++) {
        if (c >= WIN) mbar_wait(BAR_C + (c - WIN) * 8, 0);
        if (c < 8) load_idx(c); else { mbar_expect(BAR_C + c * 8, 8192); tma_load(A_PT + (c - 8) * 8192, tmb + TM_H, cta * p.NPC + (c - 8) * 64, BAR_C + c * 8); }
      }
    }
    if (tid == 448) {
      mbar_expect(BAR_W, 2 * 8192 + 2048 + 256);
      tma_load(A_W, tmb + TM_WE, 64, BAR_W); tma_load(A_W + 8192, tmb + TM_WE, 0, BAR_W); tma_load(A_W3, tmb + TM_W3, 129, BAR_W);
      bulk_load(A_WD, p.we + 128 * 64, 128, BAR_W); bulk_load(A_WD + 128, p.wx, 128, BAR_W);
    }
    __syncwarp();
  }

  const int w = wid & 3;
  const uint32_t frag = (w * 16 + (lane & 15)) * 128 + (((lane >> 4) ^ (lane & 7)) << 4), pa = A_POSH + (w * 16 + g8) * 8 + q * 2;
  float a0[32], a1[32];
  float mx = 0.f;
  auto mma = [&](float (&acc)[32], int b, int blk) {
    const uint64_t da = DHI | ((A_PT + blk * 8192) >> 4), db = DHI | ((A_W + b * 8192) >> 4);
    wg_fence();
    ss64<0>(acc, da, db); ss64<1>(acc, da + 2, db + 128); ss64<1>(acc, da + 4, db + 256); ss64<1>(acc, da + 6, db + 384);
    wg_commit();
  };
  auto epi = [&](float (&acc)[32], int b, int blk) {
    uint32_t o[16];
#pragma unroll
    for (int j = 0; j < 16; j++) o[j] = pack_f16(acc[2 * j], acc[2 * j + 1]);
    if (b) {
#pragma unroll
      for (int j = 0; j < 32; j++) mx = fmaxf(mx, fabsf(acc[j]));
    } else {
#pragma unroll
      for (int r = 0; r < 2; r++) {
        const uint32_t T = __byte_perm(lds16(pa + blk * 512 + r * 64), 0, 0x4140);
#pragma unroll
        for (int j = 0; j < 4; j++) o[2 * j + r] &= 0xFFFCFFFCu;
        const uint32_t S = o[r] + o[2 + r] * 4 + o[4 + r] * 16 + o[6 + r] * 64;
        const uint32_t X = (T - S) & 255, Y = X | ((T - ((S + X) & 0xFFFF0000u)) & 0x00FF0000u);
#pragma unroll
        for (int j = 0; j < 4; j++) o[2 * j + r] |= (Y >> (2 * j)) & 0x00030003u;
      }
    }
    const uint32_t a = (b ? A_PT : A_QS) + blk * 8192 + frag;
#pragma unroll
    for (int j = 0; j < 4; j++) stsm4(a ^ (j << 5), o[4 * j], o[4 * j + 1], o[4 * j + 2], o[4 * j + 3]);
  };
  if (wid >= 12) {
    const int node0 = cta * p.NPC, nloc = max(0, min(p.NPC, p.N - node0));
    if (w == 3) ep++;
    else {
      const int t = tid - 384;
      uint32_t ps[12], mp = 0;
#pragma unroll
      for (int k = 0; k < 4; k++) {
        ps[3 * k] = ps[3 * k + 1] = ps[3 * k + 2] = 0;
        asm volatile("{.reg .pred p; setp.lt.s32 p, %4, %5;\n @p ld.global.nc.u16 %0, [%3];\n @p ld.global.nc.u16 %1, [%3+2];\n @p ld.global.nc.u16 %2, [%3+4];}"
          : "+r"(ps[3 * k]), "+r"(ps[3 * k + 1]), "+r"(ps[3 * k + 2]) : "l"(p.pos + (size_t)(node0 + t + 96 * k) * 3), "r"(t + 96 * k), "r"(p.N - node0));
      }
      mbar_wait(BAR_W, 0);
#pragma unroll
      for (int k = 0; k < 11; k++) if (k < 10 || w < 2) { uint32_t v[4]; const uint32_t a = A_W + (t + k * 96) * 16; lds128(v, a); sts128(a, bhalf(v[0]), bhalf(v[1]), bhalf(v[2]), bhalf(v[3])); }
      const uint32_t wd = lds32(A_WD + lane * 4), md = amax_warp(wd & 0x7FFF7FFFu);
      bool bad = md - 0x3B00 > 0x680;
      if (w < 2) {
        uint32_t mw = 0;
#pragma unroll
        for (int k = 0; k < 2; k++) { uint32_t v[4]; const uint32_t a = A_W3 + (t + k * 64) * 16; lds128(v, a);
          sts128(a, b2h(bhalf(v[0])), b2h(bhalf(v[1])), b2h(bhalf(v[2])), b2h(bhalf(v[3]))); mw = amax2(amax2(amax2(amax2(mw, v[0]), v[1]), v[2]), v[3]); }
        bad |= amax_warp(mw) - 0x3B00 > 0x680;
      } else {
#pragma unroll
        for (int r = 0; r < 8; r++) sts32(A_WD2 + r * 128 + ((lane * 4) ^ (r << 4)), (r & 1) ? 0 : r == 6 ? 0xF753F753u : b2h(bhalf(wd)));
        const uint32_t x = lds32(A_WD + 128 + lane * 4), ex = min(max(amax_warp(x & 0x7FFF7FFFu) >> 7, 20u), 230u);
        const float sc = __uint_as_float((252 - ex) << 23);
        sts32(A_WD + 128 + lane * 4, pack_f16(bf_lo(x) * sc, bf_hi(x) * sc)); sts32(A_MISC + 12, (ex + 2) << 23);
      }
#pragma unroll
      for (int k = 0; k < 4; k++) {
        const int n = t + 96 * k;
        sts64(A_POSH + n * 8, pack_f16(bf_lo(ps[3 * k]), bf_lo(ps[3 * k + 1])), pack_f16(bf_lo(ps[3 * k + 2]), 1.f));
        sts16(A_POSB + n * 6, ps[3 * k]); sts16(A_POSB + n * 6 + 2, ps[3 * k + 1]); sts16(A_POSB + n * 6 + 4, ps[3 * k + 2]);
        mp = amax2(amax2(mp, ps[3 * k] | (ps[3 * k + 1] << 16)), ps[3 * k + 2]);
      }
      mp = amax_warp(mp);
      if (bad || !(bf_lo(mp) * bf_lo(mp) * bf_lo(md) < 6000.f) || (mp < 0x3B80 && (w + 1) * 32 <= nloc)) sts32(A_MISC, 1);
      proxy_fence();
      if (w == 0) STAMP(16);
      bar_arrive(3, NX + 96);
      ep++;
      bar_sync(8 + w, 160);
      if (lane == 0) {
        if (QHOLD) { mbar_wait(BAR_T + 32, 0); mbar_wait(BAR_T + 40, 0); if (QHOLD > 1) __nanosleep(QHOLD); }
        proxy_fence();
#pragma unroll
        for (int k = 0; k < 2; k++) { const int r = w * 128 + k * 64; if (r < nloc) tma_store(tmb + TM_Q, 0, node0 + r, A_QS + r * 128); }
        if (w == 2) STAMP(18);
        bulk_commit();
        asm volatile("cp.async.bulk.wait_group 0;" ::: "memory");
      }
      __syncwarp();
      if (lane < NREP) asm volatile("red.relaxed.gpu.global.add.u32 [%0], 1;" :: "l"(p.s->cnt + lane * 32) : "memory");
      if (w == 2 && lane == 0) {
        STAMP(19); mbar_arrive(BAR_A);
        if (PFD) __nanosleep(PFD);
        const uint32_t nbe = (p.E / G) & ~15u;
#pragma unroll 1
        for (int i = 0; i < PFA; i++)
          if (nbe) asm volatile("cp.async.bulk.prefetch.L2.global [%0], %1;" :: "l"((const char*)p.ea + (size_t)(i * G + cta) * nbe), "r"(nbe) : "memory");
      }
    }
    __syncwarp();
    tgb = ep << 29;
  } else {
    if (tid < (A_CNT - A_MISC) / 16) sts128(A_MISC + tid * 16, 0, tid == 0 ? 16 : 0, 0, 0);
    const uint32_t acnt = A_CNT + ((tid + cta * p.NPC) & 511) * 4;
    sts32(acnt, A_TAB + tid * (CAP * 2));
    if (tid < 32) sts32(A_CNT + 2048 + tid * 4, A_TAB + 385 * (CAP * 2));
    ep++; tgb = ep << 29;
    const uint32_t tga = (ep & 63) * 0x04000400u, tgh = tga & 0xFFFF0000u;
    {
      const uint32_t x = tga + (512 + (tid & 7) * 4) * 0x10001u;
#pragma unroll
      for (int k = 0; k < 3; k++) if (k < 2 || tid < (G + 1) * 8 - 2 * NX) {
        const uint32_t i = tid + k * NX, hw = ((i >> 3) & 31) - (i & 7) * 4;
        sts128(A_SA + i * 16, x, x + 0x10001u, x + 0x20002u, x + 0x30003u);
        sts32p(A_SA + i * 16 + hw * 4, tgh + (i & 7) * 16 + hw * 4 + 4, hw < 4);
      }
#pragma unroll
      for (int k = 0; k < 6; k++) if (k < 5 || tid < G * 16 - 5 * NX) sts128(A_SB + (tid + k * NX) * 16, tgb, tgb, tgb, tgb);
    }
    bar_sync(7, NT);
    STAMP(23);
    uint32_t d[16], oo[16], xx[16], lc[16], mxx = 0;
#pragma unroll
    for (int c = 0; c < 4; c++) {
      mbar_wait(BAR_C + c * 8, 0);
      if (c == 3) STAMP(1);
      lds128(d + 4 * c, a_dst(c) + tid * 16);
#pragma unroll
      for (int k = 4 * c; k < 4 * c + 4; k++) {
        if (tid * 16 + c * CH >= nb) d[k] = G * p.NPC;
        const uint32_t j = __umulhi(d[k], p.magic);
        xx[k] = atoms_add(A_SA + (j * 128 | ((j * 4) & 0x7C)), 258);
        oo[k] = j * 128;
      }
    }
#pragma unroll
    for (int k = 0; k < 16; k++) { oo[k] |= xx[k] & 0x7E; mxx = max(mxx, xx[k]); }
    if (mxx > tgh + 15900) {
#pragma unroll
      for (int k = 0; k < 16; k++) if (xx[k] > tgh + 15900) oo[k] = G * 128 + 64 + lane * 2;
    }
#pragma unroll
    for (int k = 0; k < 16; k++) sts16(A_SA + oo[k], (d[k] & 511) | tga);
    if (wid == 0) { bar_sync(1, NX); if (lane == 0) { proxy_fence(); tma_store_x(tmb + TM_XA, cta * 192, A_SA); bulk_commit(); } __syncwarp(); } else bar_arrive(1, NX);
    STAMP(2);
    const uint32_t eb = tgb + (tid << 18);
#pragma unroll
    for (int c = 0; c < 4; c++) {
      mbar_wait(BAR_C + 32 + c * 8, 0);
      if (wid == 0 && c == 3) STAMP(21);
      lds128(lc + 4 * c, A_SRC + c * CH + tid * 16);
#pragma unroll
      for (int k = 4 * c; k < 4 * c + 4; k++) { lc[k] += eb + ((c * NX * 4 + (k & 3)) << 16); sts32(A_SB + oo[k] * 2, lc[k]); }
    }
    bar_sync(2, NX);
    auto send_b = [&]() {
      if (tid == 0) { tma_store_x(tmb + TM_XB, cta * 96 + 32, A_SB); bulk_commit(); p.s->ep[cta * 32] = ep; }
      __syncwarp();
    };
    if (tid == 0) proxy_fence();
    if (!BL) send_b();
    STAMP(3);
    if (mxx > tgh + 15900) {
#pragma unroll
      for (int k = 0; k < 16; k++) {
        const uint32_t j = __umulhi(d[k], p.magic), r = (xx[k] - tgh) / 258 - 62;
        if (r < 31 && j < G)
          asm volatile("st.relaxed.gpu.global.v2.u32 [%0], {%1, %2};" :: "l"(p.s->xe + (j * G + cta) * 32 + r), "r"(lc[k]), "r"((d[k] & 511) | (ep << 9)) : "memory");
      }
    }
    __syncwarp();
    constexpr int JS = JSV; const int j0 = JS == 12 ? wid : (wid >> 2) * 44 + w;
#pragma unroll
    for (int k = 0; k < 7; k++) if (k < 6 || tid < 385 * CAP / 8 - 6 * NX) sts128(A_TAB + (tid + k * NX) * 16, 0, 0, 0, 0);
    bar_sync(3, NX + 96);
    STAMP(12);
    const char* xin = (const char*)(p.s->x + cta * G * 24);
    uint32_t pk[11];
    const uint32_t rot = (lane + cta) & 31;
    auto poll_a = [&]() {
#pragma unroll
      for (int k = 0; k < 11; k++) pk[k] = ldg_poll(xin + (j0 + JS * k) * FS + rot * 4);
    };
    uint32_t xs = ~0u; uint2 xv;
    const uint32_t t0 = j0 * FS + 128 + rot * 8, tx = lane ? tga : tgh;
    const uint32_t h1 = (cta & 31) * 4 + 4 + 62 * 258;
    int spin = 0;
    auto copy_b = [&]() {
      const uint32_t o = (j0 + JS * (lane >> 4)) * FS + 128 + (lane & 15) * 16;
#pragma unroll
      for (int k = 0; k < 6; k++) if (k < 5 || lane < 16)
        asm volatile("cp.async.cg.shared.global.L2::cache_hint [%0], [%1], 16, %2;" :: "r"(A_IN + o + k * 2 * JS * FS), "l"(xin + o + k * 2 * JS * FS), "l"(pol_first()) : "memory");
    };
    if (BL) { if (BL > 1) __nanosleep(BL); poll_a(); if (wid == 0) bar_sync(1, NX); else bar_arrive(1, NX); send_b(); }
#pragma unroll 1
    for (int ph = 0; ph < 2; ph++) {
      if (ph == (wid >= RF * 4)) {
        const int blk = (wid >> 2) * 2;
        mbar_wait(BAR_T + blk * 8, 0); mbar_wait(BAR_T + blk * 8 + 8, 0);
        if (wid == 8) STAMP(17);
        mma(a0, 0, blk); mma(a1, 0, blk + 1);
        asm volatile("wgmma.wait_group.sync.aligned 1;" ::: "memory"); fence_regs(a0);
        epi(a0, 0, blk);
        wg_wait0(); fence_regs(a1);
        epi(a1, 0, blk + 1);
        if (!BL) poll_a();
        bar_arrive(8 + (wid >> 2), 160);
        mma(a0, 1, blk); mma(a1, 1, blk + 1);
        wg_wait0(); fence_regs(a0); fence_regs(a1);
        bar_sync(13 + (wid >> 2), 128);
        epi(a0, 1, blk); epi(a1, 1, blk + 1);
        const uint32_t pm = __reduce_max_sync(~0u, __float_as_uint(mx));
        if (pm > 0x46000000u || (pm < 0x3A800000u && blk * 64 + (w + 1) * 16 <= min(p.NPC, p.N - cta * p.NPC))) sts32(A_MISC, 1);
        if (wid == 8) STAMP(24);
      } else {
        for (;;) {
          uint32_t mh = 0, bad = 0;
#pragma unroll
          for (int k = 0; k < 11; k++) { pk[k] ^= tx; mh = max(mh, pk[k]); bad |= pk[k]; }
          if (!__any_sync(~0u, bad & (lane ? 0xFC00FC00u : 0xFC000000u))) {
            if (__shfl_sync(~0u, mh, 0) > h1) {
              uint32_t base = 0;
#pragma unroll
              for (int k = 0; k < 11; k++) {
                const uint32_t c = (max(__shfl_sync(~0u, pk[k], 0), h1) - h1) / 258;
                if (lane - base < c) xs = (j0 + JS * k) * 32 + lane - base;
                base += c;
              }
              if (base > 31) { sts32(A_MISC, 1); xs = ~0u; }
              if (xs != ~0u) xv = ldg_poll2(p.s->xe + cta * G * 32 + xs);
              __syncwarp();
            }
            break;
          }
          if (++spin > 2000000) __trap();
          poll_a();
        }
        STAMP(14); if (wid == 8) STAMP(25);
        uint32_t r0[11], r1[11];
#pragma unroll
        for (int k = 0; k < 11; k++) {
          if (lane == 0) pk[k] = (512 + rot) * 0x10001u;
          r0[k] = atoms_add(A_CNT + (pk[k] & 0xFFFF) * 4, 2);
          r1[k] = atoms_add(A_CNT + (pk[k] >> 16) * 4, 2);
        }
#pragma unroll
        for (int k = 0; k < 11; k++) { sts16(min(r0[k], A_IN - 2), t0 + JS * k * FS); sts16(min(r1[k], A_IN - 2), t0 + JS * k * FS + 4); }
        if (wid == 8) STAMP(26);
      }
    }
    if (tid == 0) { asm volatile("cp.async.bulk.wait_group.read 0;" ::: "memory"); if (CBH) mbar_wait(BAR_T + 40, 0); mbar_arrive(BAR_X); }
    __syncwarp();
    mbar_wait(BAR_X, 0);
    copy_b();
    STAMP(4);
    if (xs != ~0u) {
      for (int i = 0; (((xv.x ^ tgb) >> 29) | ((xv.y >> 9) ^ (ep & 0x7FFFFF))) && i < 2000000; i++) xv = ldg_poll2(p.s->xe + cta * G * 32 + xs);
      const uint32_t t = (xs >> 5) * FS + 4 + (xs & 31) * 4;
      sts16(min(atoms_add(A_CNT + (xv.y & 511) * 4, 2), A_IN - 2), t);
      sts32(A_IN + t, xv.x);
    }
    __syncwarp();
    bar_sync(4, NX);
    STAMP(5);
    {
      const uint32_t dg = (lds32(acnt) - (A_TAB + tid * (CAP * 2))) >> 1;
      const uint32_t dr = atoms_add(A_DH + min(dg, 63u) * 4, 1);
      bar_sync(5, NX);
      uint32_t hb, ha; lds64(hb, ha, A_DH + (62 - 2 * lane) * 4);
      uint32_t inc = ha + hb;
#pragma unroll
      for (int o = 1; o < 32; o <<= 1) { const uint32_t y = __shfl_up_sync(~0u, inc, o); if (lane >= o) inc += y; }
      const uint32_t idx = 63 - min(dg, 63u);
      const uint32_t e2 = __shfl_sync(~0u, (inc - hb) | ((inc - hb - ha) << 16), idx >> 1);
      const uint32_t pos = ((idx & 1) ? (e2 & 0xFFFF) : (e2 >> 16)) + dr;
      sts16(A_ROWS + pos * 2, tid);
      if (!(pos & 7)) sts32(A_LEN + (pos >> 1), max(1u, (dg + 1) >> 1));
      if (dg > CAP) sts32(A_MISC, 1);
    }
    STAMP(6);
    if (tid == 0) sts32(A_IN, 0xFFFF);
    for (;;) {
      asm volatile("cp.async.wait_all;" ::: "memory");
      __syncwarp();
      uint32_t bad = 0;
#pragma unroll
      for (int k = 0; k < 11; k++) { uint32_t x, y; lds64(x, y, A_IN + t0 + JS * k * FS); bad |= (x ^ tgb) | (y ^ tgb); }
      if (!__any_sync(~0u, bad >> 29) || ++spin > 2000000) break;
      copy_b();
    }
    STAMP(7);
  }
  if (wid == 15) {
    if (lane == 0) {
      mbar_wait(BAR_A, 0);
      uint32_t c; int spin = 0;
      do { asm volatile("ld.acquire.gpu.global.u32 %0, [%1];" : "=r"(c) : "l"(p.s->cnt + (cta % NREP) * 32) : "memory"); } while ((int)(c - ep * (3 * G)) < 0 && ++spin < 20000000);
      mbar_arrive(BAR_Q);
      STAMP(20);
    }
    __syncwarp();
  }
  uint32_t W3[16], PB[16], WX[8];
#pragma unroll
  for (int k = 0; k < 4; k++) ldsm4t(W3[4 * k], W3[4 * k + 1], W3[4 * k + 2], W3[4 * k + 3], A_W3 + (lane & 15) * 128 + ((((lane >> 4) + 2 * k) ^ (lane & 7)) << 4));
#pragma unroll
  for (int j = 0; j < 8; j++) WX[j] = lds32(A_WD + 128 + j * 16 + q * 4);
  uint32_t A2[4];
  const uint32_t ring = A_RING + wid * 5120;
  const int oc = lane >> 3;
  const int r7 = lane & 7, ro = r7 >> 1, ri = 2 * (oc & 1) + (r7 & 1);
  uint64_t qp0 = (uint64_t)p.s->q + ((r7 ^ (2 * oc)) << 4), qp1 = qp0 ^ 16, epp = (uint64_t)p.ea + (((lane ^ oc) & 1) << 4) - (tgb >> 11);
  uint32_t dq = ring + oc * 512 + r7 * 16, de = ring + 2048 + ((lane * 16) ^ ((oc >> 1) * 64));
  uint32_t rq = ring + (4 * ro + ri) * 128 + (((oc >> 1) ^ r7) << 4), re = ring + 2048 + ro * 128 + ((ri ^ (2 * (ro >> 1))) << 5) + ((((oc >> 1) ^ ro) & 1) << 4);
  A2[0] = (g8 >> 1) == q ? ((g8 & 1) ? 0x3C000000u : 0x3C00u) : 0;
  A2[0] += lds32(A_MISC + 8); A2[1] = A2[0] + lds32(A_MISC + 8);
  asm volatile("" : "+l"(qp0), "+l"(qp1), "+l"(epp), "+r"(dq), "+r"(de), "+r"(rq), "+r"(re));
  if (wid < 15) { bar_sync(11, NT - 32); if (wid == 14) bar_arrive(12, 64); } else bar_sync(12, 64);
  STAMP(13);
  if (lds32(A_MISC)) { sts32(A_MISC + 12, dq ^ de ^ rq ^ re ^ (uint32_t)qp0 ^ (uint32_t)qp1 ^ (uint32_t)(epp ^ (epp >> 32)) ^ A2[1]); __syncthreads(); slow_path(p); return; }

  {
    uint32_t MS[8], acc[16], m[16], A1[4], OP, TA, D = 0, U = 0, tt, rec;
    uint64_t pol; asm("createpolicy.fractional.L2::" EPOL ".b64 %0, " EFR ";" : "=l"(pol));
    if (EKEEP) asm("createpolicy.range.global.L2::evict_unchanged.L2::evict_first.b64 %0, [%1], %2, %3;" : "=l"(pol) : "l"(p.ea), "r"(p.E * EKEEP), "r"(p.E * 32));
    const uint32_t zr = p.force_slow;
    uint32_t pv = PFB ? (wid << 24) | (wid < PFB ? 1u << (wid * PFR / 8) : 0) | (wid + 16 < PFB ? 1u << ((wid + 16) * PFR / 8) : 0) : 0;
    uint32_t mk, fq = STAT ? p.sched[wid] : wid;
    auto lane_id = []() { uint32_t l; asm volatile("mov.u32 %0, %%laneid;" : "=r"(l)); return l; };
    auto lset = [&](uint32_t id) { const uint32_t l = lane_id();
      TA = A_TAB + (id < 48 ? lds16(A_ROWS + id * 16 + (l >> 3) * 4 + (l & 2)) : 384) * (CAP * 2) + ((l >> 1) & 2); };
    auto lswitch = [&]() {
      if (STAT) {
        const uint32_t id = (fq >> (6 + 6 * __popc(mk & 6))) & 63;
        lset(id);
        if (id < 48) mk |= 8u << __shfl_sync(~0u, lds32(A_LEN + id * 4), 0);
        else if (atoms_incp(A_MISC + 4, lane_id() == 0) == 31) tail_loads(p, tmb, 63);
        __syncwarp();
        return;
      }
      const uint32_t id = __shfl_sync(~0u, atoms_incp(A_MISC + 4, lane_id() == 0), 0);
      lset(id);
      if (id < 48) { fq |= id << (6 + 6 * __popc(mk & 6)); mk |= 8u << __shfl_sync(~0u, lds32(A_LEN + id * 4), 0); }
      if ((id == HPF || id == 63) && lane_id() == 0) tail_loads(p, tmb, id);
      __syncwarp();
    };
    auto pswitch = [&]() {
      const uint32_t l = lane_id(), nd = lds16(A_ROWS + (fq & 63) * 16 + (l & 7) * 2);
      const uint32_t a = ((l & 8) ? A_WD2 + (l & 7) * 144 : A_PT + nd * 128 + ((nd & 7) << 4)) ^ (l & 16);
#pragma unroll
      for (int k = 0; k < 4; k++) ldsm4t(PB[4 * k], PB[4 * k + 1], PB[4 * k + 2], PB[4 * k + 3], a ^ (k << 5));
      OP = lds16(A_POSH + __shfl_sync(~0u, nd, l >> 2) * 8 + (l & 3) * 2) * 0x10001;
    };
    auto mswitch = [&]() {
      const uint32_t l = lane_id(), nd = lds16(A_ROWS + (fq & 63) * 16 + (l & 7) * 2), a = A_PT + nd * 128 + (((l >> 3) ^ (nd & 7)) << 4);
      uint32_t mx = U & 0x7FFF7FFFu;
#pragma unroll
      for (int j = 0; j < 8; j++) { mx = amax2(mx, MS[j]); MS[j] = h2b(MS[j]); }
      stsm4(a, MS[0], MS[1], MS[2], MS[3]); stsm4(a ^ 64, MS[4], MS[5], MS[6], MS[7]);
      const uint32_t pa = A_POSB + __shfl_sync(~0u, nd, l >> 2) * 6 + (l & 3) * 2;
      const float2 f = __half22float2(*(const __half2*)&U);
      sts16p(pa, pack_bf16(fmaf(f.x + f.y, __uint_as_float(lds32(A_MISC + 12)), bf_lo(lds16(pa))), 0.f), (l & 3) < 3);
      sts32p(A_MISC + 8, 1, ((mx + 0x04000400u) & 0x80008000u) != 0);
      U = 0;
#pragma unroll
      for (int j = 0; j < 8; j++) MS[j] = 0;
    };
    auto look = [&]() {
      asm volatile("ld.volatile.shared.u16 %0, [%1];" : "=r"(tt) : "r"(TA) : "memory"); TA += 4;
      asm volatile("ld.volatile.shared.u32 %0, [%1];" : "=r"(rec) : "r"(A_IN + tt) : "memory"); tt = __umulhi(tt, 11184811u) * p.EPC + (rec >> 16); rec &= 0xFFFF; if (ABL & 1) tt = (tt & 0x1FFFF) + 65536; };
    auto issue = [&](uint32_t st, uint32_t rec, uint32_t tt, uint32_t mk) {
      if (ABL & 2) mk &= p.force_slow;
#pragma unroll
      for (int i = 0; i < 4; i++)
        asm volatile("{.reg .b64 a; .reg .pred p, l; setp.eq.u32 p, %2, 0xFFFF; setp.ge.u32 l, %3, 8; mad.wide.u32 a, %2, 128, %1;\n @l cp.async.cg.shared.global [%0], [a], 16, p;}"
          :: "r"(dq + i * 128 + st), "l"((i & 1) ? qp1 : qp0), "r"(__shfl_sync(~0u, rec, 2 * i, 8)), "r"(mk) : "memory");
      if (!EH) asm volatile("{.reg .b64 a; .reg .pred p, l; setp.eq.u32 p, %3, 0xFFFF; setp.ge.u32 l, %4, 8; mad.wide.u32 a, %2, 32, %1;\n @l cp.async.cg.shared.global" ESZ " [%0], [a], 16, p;}"
        :: "r"(de + st), "l"(epp), "r"(tt), "r"(rec), "r"(mk) : "memory");
      else asm volatile("{.reg .b64 a; .reg .pred p, l; setp.eq.u32 p, %3, 0xFFFF; setp.ge.u32 l, %4, 8; mad.wide.u32 a, %2, 32, %1;\n @l cp.async.cg.shared.global.L2::cache_hint" ESZ " [%0], [a], 16, p, %5;}"
        :: "r"(de + st), "l"(epp), "r"(tt), "r"(rec), "r"(mk), "l"(pol) : "memory");
      asm volatile("cp.async.commit_group;" ::: "memory");
    };
    auto cfin = [&]() {
      uint32_t c0_ = 0, c1_ = 0;
#pragma unroll
      for (int k = 0; k < 4; k++) hmma(c0_, c1_, m + 4 * k, WX[2 * k], WX[2 * k + 1]);
      U = hfma(__byte_perm(c0_, c1_, 0x5410), D, U);
    };
    auto step = [&](uint32_t st) {
      if (ORD == 0 && ((mk & 9) | (pv & 1))) {
        if (PFB && (pv & 1)) {
          if (lane_id() == 0) prefetch_e(p, (pv >> 24) + PFA);
          __syncwarp();
          pv += 16 << 24;
        }
        if (mk & 1) { if (DEF) { cfin(); D = 0; } mswitch(); fq >>= 6; pswitch(); }
        if (mk & 8) lswitch();
      }
      asm volatile("cp.async.wait_group 1;" ::: "memory");
      __syncwarp();
      uint32_t E[4];
      ldsm4(E, re + st);
#pragma unroll
      for (int k = 0; k < 4; k++) ldsm4(acc + 4 * k, (rq ^ (k * 32)) + st);
      issue(st, rec, tt, mk);
      if (ORD == 0) look();
      if (ABL & 4) { U ^= (E[0] ^ acc[0] ^ acc[4] ^ acc[8] ^ acc[12]) & p.force_slow; mk >>= 1; return; }
      if (DEF == 1 && ORD != 2) cfin();
#pragma unroll
      for (int i = 0; i < 4; i++) A1[i] = b2h(E[i]);
      const uint32_t Sa = acc[0] + acc[2] * 4 + acc[4] * 16 + acc[6] * 64, Sb = acc[1] + acc[3] * 4 + acc[5] * 16 + acc[7] * 64;
      if (ORD && (mk & 9)) {
        if (mk & 1) { if (DEF && ORD == 2) { cfin(); D = 0; } mswitch(); fq >>= 6; pswitch(); }
        if (mk & 8) lswitch();
      }
      if (ORD) look();
      if (DEF && ORD == 2) cfin();
      mk >>= 1; if (PFB) pv = (pv & 0xFF000000u) | ((pv & 0xFFFFFF) >> 1);
      const uint32_t Dp = D;
      D = hsub(OP, __byte_perm(Sa, Sb, 0x6420));
      const __half2 d = *(const __half2*)&D, x = __hmul2(d, d), y = __hmul2(__high2half2(d), __high2half2(d));
      A2[2] = *(const uint32_t*)&x; A2[3] = *(const uint32_t*)&y;
      uint32_t cc[4] = {0, 0, 0, 0};
#pragma unroll
      for (int k = 0; k < 4; k++) {
#pragma unroll
        for (int j = 2 * k; j < 2 * k + 2; j++) { hmma(acc[2 * j], acc[2 * j + 1], A1, W3[2 * j], W3[2 * j + 1]); hmma(acc[2 * j], acc[2 * j + 1], A2, PB[2 * j], PB[2 * j + 1]); }
        if (DEF == 2) {
          if (k == 0) cc[1] = acc[VAR] & zr;
          hmma(cc[0], cc[1], m + 4 * k, WX[2 * k], WX[2 * k + 1]);
        }
#pragma unroll
        for (int i = 0; i < 4; i++) { m[4 * k + i] = hsilu(acc[4 * k + i]); MS[2 * k + (i >> 1)] = hadd(MS[2 * k + (i >> 1)], m[4 * k + i]); }
      }
      if (DEF == 2) U = hfma(__byte_perm(cc[0], cc[1], 0x5410), Dp, U);
      if (!DEF) cfin();
    };
#pragma unroll
    for (int i = 0; i < 16; i++) m[i] = 0;
#pragma unroll
    for (int j = 0; j < 8; j++) MS[j] = 0;
    lset(fq & 63); mk = 4u << __shfl_sync(~0u, lds32(A_LEN + (fq & 63) * 4), 0); look();
    uint32_t ra = 0, ta = 0, rb = 0, tb = 0, mb = 0;
#pragma unroll 1
    for (int k = 0; k < 2; k++) { if (mk & 8) lswitch(); ra = rb; ta = tb; rb = rec; tb = tt; mb = mk; look(); mk >>= 1; }
    if (!PSW) pswitch();
    mbar_wait(BAR_Q, 0);
    STAMP(8);
    issue(0, ra, ta, 8);
    if (PSW == 1) pswitch();
    issue(2560, rb, tb, mb);
    if (PSW == 2) pswitch();
#pragma unroll 1
    for (uint32_t st = 0;; st ^= 2560) {
      if (UNR) { step(0); if (mk == 1) break; step(2560); } else step(st);
      if (mk == 1) break;
    }
    if (DEF) cfin();
    mswitch();
  }
  STAMP(9);
  {
    int tid, cta; asm volatile("mov.u32 %0, %%tid.x;" : "=r"(tid)); asm volatile("mov.u32 %0, %%ctaid.x;" : "=r"(cta));
    const int lane = tid & 31, wg = __shfl_sync(~0u, tid >> 7, 0), node0 = cta * p.NPC, nloc = max(0, min(p.NPC, p.N - node0));
    const uint32_t frag = (((tid >> 5) & 3) * 16 + (lane & 15)) * 128 + (((lane >> 4) ^ (lane & 7)) << 4);
    const int b2 = 4 + (wg >> 1), hf = wg & 1;
    const uint64_t dW = DHI | (A_TAB >> 4), dV = dW + hf * 4;
    const uint32_t h1 = A_IN + wg * 8192, h2 = A_IN + b2 * 8192;
    float acc[32], ac2[16];
    proxy_fence();
    mbar_wait(BAR_U, 0);
    { const uint64_t dH = DHI | (h1 >> 4), dG = DHI | (h2 >> 4);
      wg_fence();
      ss64<0>(acc, dH, dW); ss64<1>(acc, dH + 2, dW + 128); ss64<1>(acc, dH + 4, dW + 256); ss64<1>(acc, dH + 6, dW + 384);
      ss32<0>(ac2, dG, dV); ss32<1>(ac2, dG + 2, dV + 128); ss32<1>(ac2, dG + 4, dV + 256); ss32<1>(ac2, dG + 6, dV + 384);
      wg_commit(); wg_wait0(); fence_regs(acc); fence_regs(ac2); }
    __syncthreads();
    STAMP(10);
    if (!ABL && lds32(A_MISC + 8)) { slow_path(p); return; }
    { const uint64_t dM = DHI | ((A_PT + wg * 8192) >> 4), dN = DHI | ((A_PT + b2 * 8192) >> 4);
      wg_fence();
      ss64<1>(acc, dM, dW + 512); ss64<1>(acc, dM + 2, dW + 640); ss64<1>(acc, dM + 4, dW + 768); ss64<1>(acc, dM + 6, dW + 896);
      wg_commit();
      for (int i = tid; i < nloc * 3; i += NT) p.out[(size_t)p.N * 64 + (size_t)node0 * 3 + i] = (uint16_t)lds16(A_POSB + i * 2);
      wg_wait0(); fence_regs(acc);
      wg_fence();
      ss32<1>(ac2, dN, dV + 512); ss32<1>(ac2, dN + 2, dV + 640); ss32<1>(ac2, dN + 4, dV + 768); ss32<1>(ac2, dN + 6, dV + 896);
      wg_commit(); }
    auto fin = [&](uint32_t x, float y0, float y1) { return badd(x, pack_bf16(silu(y0), silu(y1))); };
    auto put_block = [&](int blk, uint32_t src) {
      if (blk * 64 < nloc) tma_store((blk + 1) * 64 <= p.NPC ? tmb + TM_O : tmb + TM_O2, 0, node0 + blk * 64, src);
      bulk_commit();
    };
#pragma unroll
    for (int j = 0; j < 4; j++) {
      uint32_t x[4]; ldsm4(x, (h1 + frag) ^ (j << 5));
      stsm4((h1 + frag) ^ (j << 5), fin(x[0], acc[8 * j], acc[8 * j + 1]), fin(x[1], acc[8 * j + 2], acc[8 * j + 3]), fin(x[2], acc[8 * j + 4], acc[8 * j + 5]), fin(x[3], acc[8 * j + 6], acc[8 * j + 7]));
    }
    wg_wait0(); fence_regs(ac2);
    proxy_fence();
    bar_sync(6 + wg, 128);
    if ((tid & 127) == 0) put_block(wg, h1);
    __syncwarp();
#pragma unroll
    for (int j = 0; j < 2; j++) {
      const uint32_t a = (h2 + frag) ^ ((2 * hf + j) << 5);
      uint32_t x[4]; ldsm4(x, a);
      stsm4(a, fin(x[0], ac2[8 * j], ac2[8 * j + 1]), fin(x[1], ac2[8 * j + 2], ac2[8 * j + 3]), fin(x[2], ac2[8 * j + 4], ac2[8 * j + 5]), fin(x[3], ac2[8 * j + 6], ac2[8 * j + 7]));
    }
    proxy_fence();
    bar_sync(10 + (wg >> 1), 256);
    if ((tid & 127) == 0) {
      if (!hf) put_block(b2, h2);
      asm volatile("cp.async.bulk.wait_group.read 0;" ::: "memory");
    }
  }
  STAMP(11);
}

}

typedef CUresult (*EncodeFn)(CUtensorMap*, CUtensorMapDataType, cuuint32_t, void*, const cuuint64_t*, const cuuint64_t*, const cuuint32_t*, const cuuint32_t*,
                             CUtensorMapInterleave, CUtensorMapSwizzle, CUtensorMapL2promotion, CUtensorMapFloatOOBfill);

extern "C" void kernel_launch(void* const* d_in, const int* in_sizes, int n_in, void* d_out, int out_size) {
  Params p; Maps maps;
  p.h = (const uint16_t*)d_in[0]; p.pos = (const uint16_t*)d_in[1]; p.ea = (const uint16_t*)d_in[2];
  p.src = (const int*)d_in[3]; p.dst = (const int*)d_in[4];
  p.we = (const uint16_t*)d_in[5]; p.wx = (const uint16_t*)d_in[6]; p.wh = (const uint16_t*)d_in[7];
  p.out = (uint16_t*)d_out;
  p.N = in_sizes[0] / 64; p.E = in_sizes[3];
  p.NPC = (p.N + G - 1) / G;
  p.EPC = ((p.E + G * 4 - 1) / (G * 4)) * 4;
  p.magic = (uint32_t)((1ull << 32) / (uint64_t)p.NPC) + 1;
  const uint32_t sched[16] = {0x2d504, 0x29783, 0x2b8c2, 0x2a38b, 0x28448, 0x1f68c, 0x185d3, 0x22747, 0x2558a, 0x2e345, 0x2f9c0, 0x2c901, 0x26646, 0x216c9, 0x1c550, 0x2048f};
  for (int i = 0; i < 16; i++) p.sched[i] = sched[i] | (63u << 18);
  uint64_t al = (uint64_t)d_out;
  for (int i = 0; i < 8; i++) if (i != 1) al |= (uint64_t)d_in[i];
  p.force_slow = (al & 31) || (p.E & 3) || p.NPC > 384 || p.NPC < 2 || p.EPC > 6144;
  cudaGetSymbolAddress((void**)&p.s, g_s);
  void* fn = nullptr; cudaDriverEntryPointQueryResult qr;
  cudaGetDriverEntryPoint("cuTensorMapEncodeTiled", &fn, cudaEnableDefault, &qr);
  auto mk = [&](CUtensorMap* tm, void* base, int rows, int box) {
    const cuuint64_t dim[2] = {64, (cuuint64_t)rows}, str[1] = {128}; const cuuint32_t bx[2] = {64, (cuuint32_t)box}, es[2] = {1, 1};
    ((EncodeFn)fn)(tm, CU_TENSOR_MAP_DATA_TYPE_BFLOAT16, 2, base, dim, str, bx, es, CU_TENSOR_MAP_INTERLEAVE_NONE, CU_TENSOR_MAP_SWIZZLE_128B,
                   CU_TENSOR_MAP_L2_PROMOTION_NONE, CU_TENSOR_MAP_FLOAT_OOB_FILL_NONE);
  };
  mk(&maps.m[TM_H / 128], d_in[0], p.N, 64); mk(&maps.m[TM_WE / 128], d_in[5], 145, 64); mk(&maps.m[TM_WH / 128], d_in[7], 128, 64);
  mk(&maps.m[TM_Q / 128], p.s->q, p.N, 64); mk(&maps.m[TM_O / 128], d_out, p.N, 64); mk(&maps.m[TM_O2 / 128], d_out, p.N, (p.NPC & 63) ? (p.NPC & 63) : 64);
  mk(&maps.m[TM_W3 / 128], d_in[5], 145, 16);
  for (int k = 0; k < 2; k++) {
    const cuuint64_t dim[2] = {(cuuint64_t)G * (192 >> k), (cuuint64_t)G}, str[1] = {(cuuint64_t)G * FS}; const cuuint32_t bx[2] = {64, G}, es[2] = {1, 1};
    ((EncodeFn)fn)(&maps.m[TM_XA / 128 + k], k ? CU_TENSOR_MAP_DATA_TYPE_UINT32 : CU_TENSOR_MAP_DATA_TYPE_UINT16, 2, p.s->x, dim, str, bx, es, CU_TENSOR_MAP_INTERLEAVE_NONE,
                   CU_TENSOR_MAP_SWIZZLE_NONE, CU_TENSOR_MAP_L2_PROMOTION_NONE, CU_TENSOR_MAP_FLOAT_OOB_FILL_NONE);
  }
  cudaFuncSetAttribute(egnn_kernel, cudaFuncAttributeMaxDynamicSharedMemorySize, SMEM);
  egnn_kernel<<<G, NT, SMEM>>>(p, maps);
}
```

```cpp
#include <cuda_runtime.h>
#include <cuda_bf16.h>
#include <cuda_fp16.h>
#include <cuda.h>
#include <stdint.h>

#define PFA 6
#define HPF 99
#define CHK 8192
#define EPOL "evict_normal"
#define XPOL 2
#define ORD 0
#define WIN 6
#define RF 3
#define PFT 400
#define QHOLD 1
#define PSW 1
#define TLBW 0
#define BL 0
#define CBH 0
#define UNR 1
#define DEF 2
namespace {

constexpr int G = 132;
constexpr int NT = 512;
constexpr int CAP = 48;
constexpr int FS = 384;
constexpr uint32_t sb = 1024;

constexpr uint32_t A_RING = sb;
constexpr uint32_t A_PT = A_RING + 16 * 5120;
constexpr uint32_t A_W3 = A_PT + 49152;
constexpr uint32_t A_TAB = A_W3 + 2048;
constexpr uint32_t A_IN = A_TAB + 37888;
constexpr uint32_t A_WD = A_IN + G * FS + 512;
constexpr uint32_t A_WD2 = A_WD + 256;
constexpr uint32_t A_BAR = A_WD2 + 1024;
constexpr uint32_t A_MISC = A_BAR + 160;
constexpr uint32_t A_DH = A_MISC + 16;
constexpr uint32_t A_CNT = A_DH + 256;
constexpr uint32_t A_POSH = A_CNT + 2176;
constexpr uint32_t A_POSB = A_POSH + 3072;
constexpr uint32_t A_ROWS = A_POSB + 2304;
constexpr uint32_t A_LEN = A_ROWS + 768;
constexpr uint32_t A_END = A_LEN + 192;
constexpr int SMEM = A_END - sb;
static_assert(SMEM <= 232448 && A_TAB % 1024 == 0 && A_IN % 1024 == 0 && A_PT % 1024 == 0 && A_WD2 % 128 == 0, "smem");
constexpr int NX = 384, CH = NX * 16;
constexpr uint32_t A_QS = A_RING, A_W = A_QS + 49152, A_SA = A_IN, A_SB = A_SA + (G + 1) * 128, A_SRC = A_TAB;
__host__ __device__ constexpr uint32_t a_dst(int k) { return k < 2 ? A_W + 16384 + k * CH : A_SRC + (k + 2) * CH; }
static_assert(a_dst(1) + CH <= A_PT && a_dst(3) + CH <= A_IN && A_SB + (G + 1) * 256 <= A_WD, "staging");
constexpr uint32_t BAR_C = A_BAR, BAR_T = BAR_C + 64, BAR_W = A_BAR + 112, BAR_U = A_BAR + 120, BAR_Q = A_BAR + 128, BAR_X = A_BAR + 136, BAR_A = A_BAR + 144;

#define ABL 0
#define JSV 12
#define ESZ ""
#define VAR 0
#define STAT 1
#define PFB 0
#define PFR 3
#define EFR "1.0"
#define EKEEP 6
#define QH 5
#define QH0 0
#define PG -1
#define NREPV 8
#define PFD 0
#define EH 1
constexpr int NREP = NREPV;
struct Scratch {
  uint4 q[(G * 384 + 64) * 8];
  uint4 x[G * G * 24];
  uint2 xe[G * G * 32];
  uint32_t ep[G * 32];
  uint32_t cnt[NREP * 32];
};
__device__ __align__(256) Scratch g_s;
#define STAMP(k)

struct Maps { CUtensorMap m[9]; };
constexpr int TM_H = 0, TM_WE = 128, TM_WH = 256, TM_Q = 384, TM_O = 512, TM_O2 = 640, TM_XA = 768, TM_XB = 896, TM_W3 = 1024;
struct Params {
  const int* dst; const int* src; int E, EPC, force_slow, NPC; Scratch* s; int N; uint32_t magic;
  const uint16_t* h; const uint16_t* pos; const uint16_t* ea; const uint16_t* we; const uint16_t* wx; const uint16_t* wh; uint16_t* out;
  uint32_t sched[16];
};

#define R32(d) "+f"(d[0]),"+f"(d[1]),"+f"(d[2]),"+f"(d[3]),"+f"(d[4]),"+f"(d[5]),"+f"(d[6]),"+f"(d[7]),"+f"(d[8]),"+f"(d[9]),"+f"(d[10]),"+f"(d[11]),"+f"(d[12]),"+f"(d[13]),"+f"(d[14]),"+f"(d[15]),"+f"(d[16]),"+f"(d[17]),"+f"(d[18]),"+f"(d[19]),"+f"(d[20]),"+f"(d[21]),"+f"(d[22]),"+f"(d[23]),"+f"(d[24]),"+f"(d[25]),"+f"(d[26]),"+f"(d[27]),"+f"(d[28]),"+f"(d[29]),"+f"(d[30]),"+f"(d[31])
#define S32 "{%0,%1,%2,%3,%4,%5,%6,%7,%8,%9,%10,%11,%12,%13,%14,%15,%16,%17,%18,%19,%20,%21,%22,%23,%24,%25,%26,%27,%28,%29,%30,%31}"
#define R16(d) "+f"(d[0]),"+f"(d[1]),"+f"(d[2]),"+f"(d[3]),"+f"(d[4]),"+f"(d[5]),"+f"(d[6]),"+f"(d[7]),"+f"(d[8]),"+f"(d[9]),"+f"(d[10]),"+f"(d[11]),"+f"(d[12]),"+f"(d[13]),"+f"(d[14]),"+f"(d[15])
#define S16 "{%0,%1,%2,%3,%4,%5,%6,%7,%8,%9,%10,%11,%12,%13,%14,%15}"
#define DI __device__ __forceinline__

constexpr uint64_t DHI = (64ull << 32) | (1ull << 62);
template<int SD> DI void ss64(float (&d)[32], uint64_t da, uint64_t db) {
  asm volatile("wgmma.mma_async.sync.aligned.m64n64k16.f32.bf16.bf16 " S32 ", %32, %33, %34, 1, 1, 0, 1;" : R32(d) : "l"(da), "l"(db), "n"(SD)); }
template<int SD> DI void rs64(float (&d)[32], const uint32_t* a, uint64_t db) {
  asm volatile("wgmma.mma_async.sync.aligned.m64n64k16.f32.bf16.bf16 " S32 ", {%32,%33,%34,%35}, %36, %37, 1, 1, 1;" : R32(d) : "r"(a[0]), "r"(a[1]), "r"(a[2]), "r"(a[3]), "l"(db), "n"(SD)); }
DI void wg_fence() { asm volatile("wgmma.fence.sync.aligned;" ::: "memory"); }
DI void wg_commit() { asm volatile("wgmma.commit_group.sync.aligned;" ::: "memory"); }
DI void wg_wait0() { asm volatile("wgmma.wait_group.sync.aligned 0;" ::: "memory"); }
DI void fence_regs(float (&d)[32]) { asm volatile("" : R32(d) :: "memory"); }
DI void fence_regs(float (&d)[16]) { asm volatile("" : R16(d) :: "memory"); }
DI void proxy_fence() { asm volatile("fence.proxy.async.shared::cta;" ::: "memory"); }
DI void hmma(uint32_t& d0, uint32_t& d1, const uint32_t* a, uint32_t b0, uint32_t b1) {
  asm("mma.sync.aligned.m16n8k16.row.col.f16.f16.f16.f16 {%0,%1}, {%2,%3,%4,%5}, {%6,%7}, {%0,%1};" : "+r"(d0), "+r"(d1) : "r"(a[0]), "r"(a[1]), "r"(a[2]), "r"(a[3]), "r"(b0), "r"(b1)); }
DI uint64_t pol_first() { uint64_t r; asm("createpolicy.fractional.L2::evict_first.b64 %0, 1.0;" : "=l"(r)); return r; }
DI float tanh_ap(float x) { float y; asm("tanh.approx.f32 %0, %1;" : "=f"(y) : "f"(x)); return y; }
DI float silu(float x) { const float y = 0.5f * x; return fmaf(y, tanh_ap(y), y); }
DI uint32_t pack_bf16(float lo, float hi) { uint32_t r; asm("cvt.rn.bf16x2.f32 %0, %1, %2;" : "=r"(r) : "f"(hi), "f"(lo)); return r; }
DI uint32_t pack_f16(float lo, float hi) { uint32_t r; asm("cvt.rn.f16x2.f32 %0, %1, %2;" : "=r"(r) : "f"(hi), "f"(lo)); return r; }
DI float bf_lo(uint32_t v) { return __uint_as_float(v << 16); }
DI float bf_hi(uint32_t v) { return __uint_as_float(v & 0xFFFF0000u); }
DI uint32_t b2h(uint32_t v) { return pack_f16(bf_lo(v), bf_hi(v)); }
DI uint32_t h2b(uint32_t v) { const float2 f = __half22float2(*(const __half2*)&v); return pack_bf16(f.x, f.y); }
DI uint32_t hadd(uint32_t a, uint32_t b) { uint32_t r; asm("add.rn.f16x2 %0, %1, %2;" : "=r"(r) : "r"(a), "r"(b)); return r; }
DI uint32_t hsub(uint32_t a, uint32_t b) { uint32_t r; asm("sub.rn.f16x2 %0, %1, %2;" : "=r"(r) : "r"(a), "r"(b)); return r; }
DI uint32_t hfma(uint32_t a, uint32_t b, uint32_t c) { uint32_t r; asm("fma.rn.f16x2 %0, %1, %2, %3;" : "=r"(r) : "r"(a), "r"(b), "r"(c)); return r; }
DI uint32_t hsilu(uint32_t y) { uint32_t t; asm("tanh.approx.f16x2 %0, %1;" : "=r"(t) : "r"(y)); return hfma(y, t, y); }
DI uint32_t badd(uint32_t a, uint32_t b) { uint32_t r; asm("add.rn.bf16x2 %0, %1, %2;" : "=r"(r) : "r"(a), "r"(b)); return r; }
DI uint32_t bhalf(uint32_t v) { uint32_t r; asm("mul.rn.bf16x2 %0, %1, %2;" : "=r"(r) : "r"(v), "r"(0x3F003F00u)); return r; }
DI uint32_t amax2(uint32_t mx, uint32_t v) { return __vmaxu2(mx, v & 0x7FFF7FFFu); }
DI uint32_t amax_warp(uint32_t mx) { return __reduce_max_sync(~0u, max(mx & 0xFFFF, mx >> 16)); }
DI void mbar_wait(uint32_t bar, uint32_t parity) {
  asm volatile("{.reg .pred p; .reg .u32 c; mov.u32 c, 0;\n"
    "LW_%=: mbarrier.try_wait.parity.shared::cta.b64 p, [%0], %1;\n"
    "@p bra.uni LD_%=;\n add.u32 c, c, 1; setp.lt.u32 p, c, 20000000;\n @p bra.uni LW_%=;\n LD_%=:}" :: "r"(bar), "r"(parity) : "memory");
}
DI void mbar_arrive(uint32_t bar) { asm volatile("mbarrier.arrive.shared::cta.b64 _, [%0];" :: "r"(bar) : "memory"); }
DI void bar_sync(int id, int n) { asm volatile("bar.sync %0, %1;" :: "r"(id), "r"(n) : "memory"); }
DI void bar_arrive(int id, int n) { asm volatile("bar.arrive %0, %1;" :: "r"(id), "r"(n) : "memory"); }
DI void sts128(uint32_t a, uint32_t x, uint32_t y, uint32_t z, uint32_t w) { asm volatile("st.shared.v4.u32 [%0], {%1,%2,%3,%4};" :: "r"(a), "r"(x), "r"(y), "r"(z), "r"(w) : "memory"); }
DI void sts64(uint32_t a, uint32_t x, uint32_t y) { asm volatile("st.shared.v2.u32 [%0], {%1,%2};" :: "r"(a), "r"(x), "r"(y) : "memory"); }
DI void sts32(uint32_t a, uint32_t x) { asm volatile("st.shared.u32 [%0], %1;" :: "r"(a), "r"(x) : "memory"); }
DI void sts16(uint32_t a, uint32_t x) { asm volatile("st.shared.u16 [%0], %1;" :: "r"(a), "h"((uint16_t)x) : "memory"); }
DI void sts32p(uint32_t a, uint32_t x, bool p) { asm volatile("{.reg .pred p; setp.ne.b32 p, %2, 0; @p st.shared.u32 [%0], %1;}" :: "r"(a), "r"(x), "r"((int)p) : "memory"); }
DI void sts16p(uint32_t a, uint32_t x, bool p) { asm volatile("{.reg .pred p; setp.ne.b32 p, %2, 0; @p st.shared.u16 [%0], %1;}" :: "r"(a), "h"((uint16_t)x), "r"((int)p) : "memory"); }
DI void lds128(uint32_t* v, uint32_t a) { asm volatile("ld.shared.v4.u32 {%0, %1, %2, %3}, [%4];" : "=r"(v[0]), "=r"(v[1]), "=r"(v[2]), "=r"(v[3]) : "r"(a) : "memory"); }
DI void lds64(uint32_t& x, uint32_t& y, uint32_t a) { asm volatile("ld.shared.v2.u32 {%0, %1}, [%2];" : "=r"(x), "=r"(y) : "r"(a) : "memory"); }
DI uint32_t lds32(uint32_t a) { uint32_t x; asm volatile("ld.shared.u32 %0, [%1];" : "=r"(x) : "r"(a) : "memory"); return x; }
DI uint32_t lds16(uint32_t a) { uint32_t x; asm volatile("ld.shared.u16 %0, [%1];" : "=r"(x) : "r"(a) : "memory"); return x; }
DI uint32_t atoms_add(uint32_t a, uint32_t v) { uint32_t r; asm volatile("atom.shared.add.u32 %0, [%1], %2;" : "=r"(r) : "r"(a), "r"(v) : "memory"); return r; }
DI uint32_t atoms_incp(uint32_t a, bool p) { uint32_t r = 0; asm volatile("{.reg .pred p; setp.ne.b32 p, %2, 0; @p atom.shared.add.u32 %0, [%1], 1;}" : "+r"(r) : "r"(a), "r"((int)p) : "memory"); return r; }
DI uint32_t ldg_poll(const void* a) { uint32_t x; asm volatile("ld.relaxed.gpu.global.u32 %0, [%1];" : "=r"(x) : "l"(a) : "memory"); return x; }
DI uint2 ldg_poll2(const void* a) { uint2 x; asm volatile("ld.relaxed.gpu.global.v2.u32 {%0, %1}, [%2];" : "=r"(x.x), "=r"(x.y) : "l"(a) : "memory"); return x; }
DI void bulk_load(uint32_t dst, const void* src, uint32_t bytes, uint32_t bar) {
  asm volatile("cp.async.bulk.shared::cluster.global.mbarrier::complete_tx::bytes.L2::cache_hint [%0], [%1], %2, [%3], %4;" :: "r"(dst), "l"(src), "r"(bytes), "r"(bar), "l"(pol_first()) : "memory"); }
DI void mbar_expect(uint32_t bar, uint32_t bytes) { asm volatile("mbarrier.arrive.expect_tx.shared::cta.b64 _, [%0], %1;" :: "r"(bar), "r"(bytes) : "memory"); }
DI void mbar_init(uint32_t bar, int n) { asm volatile("mbarrier.init.shared::cta.b64 [%0], %1;" :: "r"(bar), "r"(n) : "memory"); }
DI void tma_load(uint32_t dst, uint64_t tm, int row, uint32_t bar) {
  asm volatile("cp.async.bulk.tensor.2d.shared::cluster.global.mbarrier::complete_tx::bytes.L2::cache_hint [%0], [%1, {%3, %4}], [%2], %5;" :: "r"(dst), "l"(tm), "r"(bar), "r"(0), "r"(row), "l"(pol_first()) : "memory"); }
DI void tma_store(uint64_t tm, int col, int row, uint32_t src) {
  asm volatile("cp.async.bulk.tensor.2d.global.shared::cta.bulk_group [%0, {%2, %3}], [%1];" :: "l"(tm), "r"(src), "r"(col), "r"(row) : "memory"); }
DI void tma_store_x(uint64_t tm, int col, uint32_t src) {
  if (XPOL & 1) asm volatile("cp.async.bulk.tensor.2d.global.shared::cta.bulk_group.L2::cache_hint [%0, {%2, 0}], [%1], %3;" :: "l"(tm), "r"(src), "r"(col), "l"(pol_first()) : "memory");
  else tma_store(tm, col, 0, src); }
DI void bulk_commit() { asm volatile("cp.async.bulk.commit_group;" ::: "memory"); }
DI void stsm4(uint32_t a, uint32_t x, uint32_t y, uint32_t z, uint32_t w) { asm volatile("stmatrix.sync.aligned.m8n8.x4.shared.b16 [%0], {%1,%2,%3,%4};" :: "r"(a), "r"(x), "r"(y), "r"(z), "r"(w) : "memory"); }
DI void ldsm4(uint32_t* v, uint32_t a) { asm volatile("ldmatrix.sync.aligned.m8n8.x4.shared.b16 {%0,%1,%2,%3}, [%4];" : "=r"(v[0]), "=r"(v[1]), "=r"(v[2]), "=r"(v[3]) : "r"(a) : "memory"); }
DI void ldsm4t(uint32_t& x, uint32_t& y, uint32_t& z, uint32_t& w, uint32_t a) { asm volatile("ldmatrix.sync.aligned.m8n8.x4.trans.shared.b16 {%0,%1,%2,%3}, [%4];" : "=r"(x), "=r"(y), "=r"(z), "=r"(w) : "r"(a) : "memory"); }

__device__ __noinline__ void slow_path(const Params& p) {
  const int lane = threadIdx.x & 31, wid = threadIdx.x >> 5;
  const uint32_t ab = sb + wid * (24 * 528);
  const uint32_t* we = (const uint32_t*)p.we;
  const int nend = min(p.N, (blockIdx.x + 1) * p.NPC);
  auto rowmul = [&](uint32_t hv, const uint32_t* w, float& y0, float& y1) {
#pragma unroll 4
    for (int k = 0; k < 32; k++) {
      const uint32_t hk = __shfl_sync(~0u, hv, k), wa = __ldg(w + 2 * k * 32 + lane), wb = __ldg(w + (2 * k + 1) * 32 + lane);
      y0 = fmaf(bf_lo(hk), bf_lo(wa), fmaf(bf_hi(hk), bf_lo(wb), y0)); y1 = fmaf(bf_lo(hk), bf_hi(wa), fmaf(bf_hi(hk), bf_hi(wb), y1));
    }
  };
  auto act = [](float x) { return x / (1.f + __expf(-x)); };
  auto hrow = [&](int n) { return __ldg(p.h + (size_t)n * 64 + 2 * lane) | ((uint32_t)__ldg(p.h + (size_t)n * 64 + 2 * lane + 1) << 16); };
  const uint32_t wdv = __ldg(we + 128 * 32 + lane), wxv = __ldg((const uint32_t*)p.wx + lane);
  for (int nb = blockIdx.x * p.NPC + wid * 24; nb < nend; nb += 384) {
    const int cnt = min(24, nend - nb);
    for (int n = 0; n < cnt; n++) {
      float y0 = 0.f, y1 = 0.f; rowmul(hrow(nb + n), we, y0, y1);
      sts64(ab + n * 528 + lane * 8, 0, 0); sts64(ab + n * 528 + 256 + lane * 8, __float_as_uint(y0), __float_as_uint(y1));
      if (lane < 4) sts32(ab + n * 528 + 512 + lane * 4, 0);
    }
    __syncwarp();
    for (int base = 0; base < p.E; base += 32) {
      const uint32_t dl = base + lane < p.E ? (uint32_t)(__ldg(p.dst + base + lane) - nb) : 0xFFFFFFFFu;
      uint32_t mk = __ballot_sync(~0u, dl < (uint32_t)cnt);
      while (mk) {
        const int l = __ffs(mk) - 1; mk &= mk - 1;
        const int e = base + l, n = __shfl_sync(~0u, dl, l), s = __ldg(p.src + e);
        const uint32_t a = ab + n * 528;
        float df = 0.f;
        if (lane < 3) df = bf_lo(pack_bf16(bf_lo(__ldg(p.pos + (size_t)(nb + n) * 3 + lane)) - bf_lo(__ldg(p.pos + (size_t)s * 3 + lane)), 0.f));
        float d2 = df * df; d2 += __shfl_xor_sync(~0u, d2, 1); d2 += __shfl_xor_sync(~0u, d2, 2); d2 = __shfl_sync(~0u, d2, 0);
        uint32_t x0, x1; lds64(x0, x1, a + 256 + lane * 8);
        float y0 = fmaf(d2, bf_lo(wdv), __uint_as_float(x0)), y1 = fmaf(d2, bf_hi(wdv), __uint_as_float(x1));
        rowmul(hrow(s), we + 64 * 32, y0, y1);
        for (int k = 0; k < 16; k++) { const float ev = bf_lo(__ldg(p.ea + (size_t)e * 16 + k)); const uint32_t w = __ldg(we + (129 + k) * 32 + lane); y0 = fmaf(ev, bf_lo(w), y0); y1 = fmaf(ev, bf_hi(w), y1); }
        y0 = act(y0); y1 = act(y1);
        float c = y0 * bf_lo(wxv) + y1 * bf_hi(wxv);
#pragma unroll
        for (int o = 16; o; o >>= 1) c += __shfl_xor_sync(~0u, c, o);
        lds64(x0, x1, a + lane * 8);
        sts64(a + lane * 8, __float_as_uint(__uint_as_float(x0) + y0), __float_as_uint(__uint_as_float(x1) + y1));
        if (lane < 3) sts32(a + 512 + lane * 4, __float_as_uint(fmaf(c, df, __uint_as_float(lds32(a + 512 + lane * 4)))));
      }
    }
    __syncwarp();
    for (int n = 0; n < cnt; n++) {
      const uint32_t hv = hrow(nb + n); uint32_t x0, x1; lds64(x0, x1, ab + n * 528 + lane * 8);
      float y0 = 0.f, y1 = 0.f; rowmul(hv, (const uint32_t*)p.wh, y0, y1); rowmul(pack_bf16(__uint_as_float(x0), __uint_as_float(x1)), (const uint32_t*)p.wh + 64 * 32, y0, y1);
      const uint32_t o = badd(hv, pack_bf16(act(y0), act(y1)));
      p.out[(size_t)(nb + n) * 64 + 2 * lane] = (uint16_t)o; p.out[(size_t)(nb + n) * 64 + 2 * lane + 1] = (uint16_t)(o >> 16);
      if (lane < 3) p.out[(size_t)p.N * 64 + (size_t)(nb + n) * 3 + lane] = (uint16_t)pack_bf16(bf_lo(__ldg(p.pos + (size_t)(nb + n) * 3 + lane)) + __uint_as_float(lds32(ab + n * 528 + 512 + lane * 4)), 0.f);
    }
    __syncwarp();
  }
}

__global__ void __launch_bounds__(NT, 1) egnn_kernel(const __grid_constant__ Params p, const __grid_constant__ Maps maps) {
  extern __shared__ __align__(1024) unsigned char smraw[];
  const int tid = threadIdx.x, cta = blockIdx.x;
  const int e0 = cta * p.EPC, nb = max(0, min(p.EPC, p.E - e0)) * 4;
  STAMP(0);
  auto load_idx = [&](int c) {
    const int o = (c & 3) * CH, n = max(0, min(CH, nb - o));
    mbar_expect(BAR_C + c * 8, n);
    if (n) bulk_load(c < 4 ? a_dst(c) : A_SRC + o, (const char*)((c < 4 ? p.dst : p.src) + e0) + o, n, BAR_C + c * 8);
  };
  if (tid == 480 && !p.force_slow) {
#pragma unroll
    for (int c = 0; c < 4; c++) mbar_init(BAR_C + c * 8, 1);
    asm volatile("fence.mbarrier_init.release.cluster;" ::: "memory");
#pragma unroll
    for (int c = 0; c < 4; c++) load_idx(c);
  }
  if ((uint32_t)__cvta_generic_to_shared(smraw) != sb) return;
  if (p.force_slow) { slow_path(p); return; }
  uint32_t ep = ldg_poll(p.s->ep + cta * 32), tgb;
  const uint64_t tmb = (uint64_t)&maps;
  const int lane = tid & 31, wid = __shfl_sync(~0u, tid >> 5, 0), g8 = lane >> 2, q = lane & 3;
  if (wid >= 12) {
    if (tid == 480 || tid == 448) {
#pragma unroll
      for (int c = 0; c < 10; c++) if (tid == 480 || c < 5) mbar_init(BAR_C + (tid == 480 ? 32 : 112) + c * 8, 1);
      asm volatile("fence.mbarrier_init.release.cluster;" ::: "memory");
    }
    if (tid - 416 < 9u) asm volatile("prefetch.tensormap [%0];" :: "l"(tmb + (tid - 416) * 128));
    __syncwarp();
    if (wid == 15) bar_arrive(7, NT); else bar_sync(7, NT);
    if (tid == 480) {
#pragma unroll 1
      for (int c = 4; c < 14; c++) {
        if (c >= WIN) mbar_wait(BAR_C + (c - WIN) * 8, 0);
        if (c < 8) load_idx(c); else { mbar_expect(BAR_C + c * 8, 8192); tma_load(A_PT + (c - 8) * 8192, tmb + TM_H, cta * p.NPC + (c - 8) * 64, BAR_C + c * 8); }
      }
    }
    if (tid == 448) {
      mbar_expect(BAR_W, 2 * 8192 + 2048 + 256);
      tma_load(A_W, tmb + TM_WE, 64, BAR_W); tma_load(A_W + 8192, tmb + TM_WE, 0, BAR_W); tma_load(A_W3, tmb + TM_W3, 129, BAR_W);
      bulk_load(A_WD, p.we + 128 * 64, 128, BAR_W); bulk_load(A_WD + 128, p.wx, 128, BAR_W);
    }
    __syncwarp();
  }

  const int w = wid & 3;
  const uint32_t frag = (w * 16 + (lane & 15)) * 128 + (((lane >> 4) ^ (lane & 7)) << 4), pa = A_POSH + (w * 16 + g8) * 8 + q * 2;
  float a0[32], a1[32];
  float mx = 0.f;
  auto mma = [&](float (&acc)[32], int b, int blk) {
    const uint64_t da = DHI | ((A_PT + blk * 8192) >> 4), db = DHI | ((A_W + b * 8192) >> 4);
    wg_fence();
    ss64<0>(acc, da, db); ss64<1>(acc, da + 2, db + 128); ss64<1>(acc, da + 4, db + 256); ss64<1>(acc, da + 6, db + 384);
    wg_commit();
  };
  auto epi = [&](float (&acc)[32], int b, int blk) {
    uint32_t o[16];
#pragma unroll
    for (int j = 0; j < 16; j++) o[j] = pack_f16(acc[2 * j], acc[2 * j + 1]);
    if (b) {
#pragma unroll
      for (int j = 0; j < 32; j++) mx = fmaxf(mx, fabsf(acc[j]));
    } else {
#pragma unroll
      for (int r = 0; r < 2; r++) {
        const uint32_t T = __byte_perm(lds16(pa + blk * 512 + r * 64), 0, 0x4140);
#pragma unroll
        for (int j = 0; j < 4; j++) o[2 * j + r] &= 0xFFFCFFFCu;
        const uint32_t S = o[r] + o[2 + r] * 4 + o[4 + r] * 16 + o[6 + r] * 64;
        const uint32_t X = (T - S) & 255, Y = X | ((T - ((S + X) & 0xFFFF0000u)) & 0x00FF0000u);
#pragma unroll
        for (int j = 0; j < 4; j++) o[2 * j + r] |= (Y >> (2 * j)) & 0x00030003u;
      }
    }
    const uint32_t a = (b ? A_PT : A_QS) + blk * 8192 + frag;
#pragma unroll
    for (int j = 0; j < 4; j++) stsm4(a ^ (j << 5), o[4 * j], o[4 * j + 1], o[4 * j + 2], o[4 * j + 3]);
  };
  auto p_check = [&](int blk) {
    const uint32_t pm = __reduce_max_sync(~0u, __float_as_uint(mx));
    if (pm > 0x46000000u || (pm < 0x3A800000u && blk * 64 + (w + 1) * 16 <= min(p.NPC, p.N - cta * p.NPC))) sts32(A_MISC, 1);
  };
  if (wid >= 12) {
    const int node0 = cta * p.NPC, nloc = max(0, min(p.NPC, p.N - node0));
    if (w == 3) ep++;
    else {
      const int t = tid - 384;
      uint32_t ps[12], mp = 0;
#pragma unroll
      for (int k = 0; k < 4; k++) {
        ps[3 * k] = ps[3 * k + 1] = ps[3 * k + 2] = 0;
        asm volatile("{.reg .pred p; setp.lt.s32 p, %4, %5;\n @p ld.global.nc.u16 %0, [%3];\n @p ld.global.nc.u16 %1, [%3+2];\n @p ld.global.nc.u16 %2, [%3+4];}"
          : "+r"(ps[3 * k]), "+r"(ps[3 * k + 1]), "+r"(ps[3 * k + 2]) : "l"(p.pos + (size_t)(node0 + t + 96 * k) * 3), "r"(t + 96 * k), "r"(p.N - node0));
      }
      mbar_wait(BAR_W, 0);
#pragma unroll
      for (int k = 0; k < 11; k++) if (k < 10 || w < 2) { uint32_t v[4]; const uint32_t a = A_W + (t + k * 96) * 16; lds128(v, a); sts128(a, bhalf(v[0]), bhalf(v[1]), bhalf(v[2]), bhalf(v[3])); }
      const uint32_t wd = lds32(A_WD + lane * 4), md = amax_warp(wd & 0x7FFF7FFFu);
      bool bad = md - 0x3B00 > 0x680;
      if (w < 2) {
        uint32_t mw = 0;
#pragma unroll
        for (int k = 0; k < 2; k++) { uint32_t v[4]; const uint32_t a = A_W3 + (t + k * 64) * 16; lds128(v, a);
          sts128(a, b2h(bhalf(v[0])), b2h(bhalf(v[1])), b2h(bhalf(v[2])), b2h(bhalf(v[3]))); mw = amax2(amax2(amax2(amax2(mw, v[0]), v[1]), v[2]), v[3]); }
        bad |= amax_warp(mw) - 0x3B00 > 0x680;
      } else {
#pragma unroll
        for (int r = 0; r < 8; r++) sts32(A_WD2 + r * 128 + ((lane * 4) ^ (r << 4)), (r & 1) ? 0 : r == 6 ? 0xF753F753u : b2h(bhalf(wd)));
        const uint32_t x = lds32(A_WD + 128 + lane * 4), ex = min(max(amax_warp(x & 0x7FFF7FFFu) >> 7, 20u), 230u);
        const float sc = __uint_as_float((252 - ex) << 23);
        sts32(A_WD + 128 + lane * 4, pack_f16(bf_lo(x) * sc, bf_hi(x) * sc)); sts32(A_MISC + 12, (ex + 2) << 23);
      }
#pragma unroll
      for (int k = 0; k < 4; k++) {
        const int n = t + 96 * k;
        sts64(A_POSH + n * 8, pack_f16(bf_lo(ps[3 * k]), bf_lo(ps[3 * k + 1])), pack_f16(bf_lo(ps[3 * k + 2]), 1.f));
        sts16(A_POSB + n * 6, ps[3 * k]); sts16(A_POSB + n * 6 + 2, ps[3 * k + 1]); sts16(A_POSB + n * 6 + 4, ps[3 * k + 2]);
        mp = amax2(amax2(mp, ps[3 * k] | (ps[3 * k + 1] << 16)), ps[3 * k + 2]);
      }
      mp = amax_warp(mp);
      if (bad || !(bf_lo(mp) * bf_lo(mp) * bf_lo(md) < 6000.f) || (mp < 0x3B80 && (w + 1) * 32 <= nloc)) sts32(A_MISC, 1);
      proxy_fence();
      if (w == 0) STAMP(16);
      bar_arrive(3, NX + 96);
      ep++;
    }
    bar_sync(6, 128);
    auto store_q = [&](int lo, int hi) {
      if (lane == 0) {
        proxy_fence();
#pragma unroll 1
        for (int b = lo; b < hi && b * 64 < nloc; b++) tma_store(tmb + TM_Q, 0, node0 + b * 64, A_QS + b * 8192);
      }
      __syncwarp();
    };
#pragma unroll 1
    for (int blk = 0; blk < 6; blk += blk ? 1 : 4) {
      mbar_wait(BAR_T + blk * 8, 0);
      if (w == 0 && blk == 5) STAMP(17);
      mma(a0, 0, blk); mma(a1, 1, blk);
      if (w == 3 && blk == QH) { bar_sync(8, NX + 32); store_q(QH0, QH); }
      asm volatile("wgmma.wait_group.sync.aligned 1;" ::: "memory"); fence_regs(a0);
      epi(a0, 0, blk);
      wg_wait0(); fence_regs(a1);
      bar_sync(6, 128);
      if (w == 3 && (blk >= QH || blk < QH0)) store_q(blk, blk + 1);
      if (w == 3) STAMP(18);
      epi(a1, 1, blk);
    }
    p_check(0);
    tgb = ep << 29;
  } else {
    if (tid < (A_CNT - A_MISC) / 16) sts128(A_MISC + tid * 16, 0, tid == 0 ? 16 : 0, 0, 0);
    const uint32_t acnt = A_CNT + ((tid + cta * p.NPC) & 511) * 4;
    sts32(acnt, A_TAB + tid * (CAP * 2));
    if (tid < 32) sts32(A_CNT + 2048 + tid * 4, A_TAB + 385 * (CAP * 2));
    ep++; tgb = ep << 29;
    const uint32_t tga = (ep & 63) * 0x04000400u, tgh = tga & 0xFFFF0000u;
    {
      const uint32_t x = tga + (512 + (tid & 7) * 4) * 0x10001u;
#pragma unroll
      for (int k = 0; k < 3; k++) if (k < 2 || tid < (G + 1) * 8 - 2 * NX) {
        const uint32_t i = tid + k * NX, hw = ((i >> 3) & 31) - (i & 7) * 4;
        sts128(A_SA + i * 16, x, x + 0x10001u, x + 0x20002u, x + 0x30003u);
        sts32p(A_SA + i * 16 + hw * 4, tgh + (i & 7) * 16 + hw * 4 + 4, hw < 4);
      }
#pragma unroll
      for (int k = 0; k < 6; k++) if (k < 5 || tid < G * 16 - 5 * NX) sts128(A_SB + (tid + k * NX) * 16, tgb, tgb, tgb, tgb);
    }
    bar_sync(7, NT);
    STAMP(23);
    uint32_t d[16], oo[16], xx[16], lc[16], mxx = 0;
#pragma unroll
    for (int c = 0; c < 4; c++) {
      mbar_wait(BAR_C + c * 8, 0);
      if (c == 3) STAMP(1);
      lds128(d + 4 * c, a_dst(c) + tid * 16);
#pragma unroll
      for (int k = 4 * c; k < 4 * c + 4; k++) {
        if (tid * 16 + c * CH >= nb) d[k] = G * p.NPC;
        const uint32_t j = __umulhi(d[k], p.magic);
        xx[k] = atoms_add(A_SA + (j * 128 | ((j * 4) & 0x7C)), 258);
        oo[k] = j * 128;
      }
    }
#pragma unroll
    for (int k = 0; k < 16; k++) { oo[k] |= xx[k] & 0x7E; mxx = max(mxx, xx[k]); }
    if (mxx > tgh + 15900) {
#pragma unroll
      for (int k = 0; k < 16; k++) if (xx[k] > tgh + 15900) oo[k] = G * 128 + 64 + lane * 2;
    }
#pragma unroll
    for (int k = 0; k < 16; k++) sts16(A_SA + oo[k], (d[k] & 511) | tga);
    if (wid == 0) { bar_sync(1, NX); if (lane == 0) { proxy_fence(); tma_store_x(tmb + TM_XA, cta * 192, A_SA); bulk_commit(); } __syncwarp(); } else bar_arrive(1, NX);
    STAMP(2);
    const uint32_t eb = tgb + (tid << 18);
#pragma unroll
    for (int c = 0; c < 4; c++) {
      mbar_wait(BAR_C + 32 + c * 8, 0);
      if (wid == 0 && c == 3) STAMP(21);
      lds128(lc + 4 * c, A_SRC + c * CH + tid * 16);
#pragma unroll
      for (int k = 4 * c; k < 4 * c + 4; k++) { lc[k] += eb + ((c * NX * 4 + (k & 3)) << 16); sts32(A_SB + oo[k] * 2, lc[k]); }
    }
    bar_sync(2, NX);
    if (tid == 0) { proxy_fence(); tma_store_x(tmb + TM_XB, cta * 96 + 32, A_SB); bulk_commit(); p.s->ep[cta * 32] = ep; }
    __syncwarp();
    STAMP(3);
    if (mxx > tgh + 15900) {
#pragma unroll
      for (int k = 0; k < 16; k++) {
        const uint32_t j = __umulhi(d[k], p.magic), r = (xx[k] - tgh) / 258 - 62;
        if (r < 31 && j < G)
          asm volatile("st.relaxed.gpu.global.v2.u32 [%0], {%1, %2};" :: "l"(p.s->xe + (j * G + cta) * 32 + r), "r"(lc[k]), "r"((d[k] & 511) | (ep << 9)) : "memory");
      }
    }
    __syncwarp();
    constexpr int JS = JSV; const int j0 = JS == 12 ? wid : (wid >> 2) * 44 + w;
#pragma unroll
    for (int k = 0; k < 7; k++) if (k < 6 || tid < 385 * CAP / 8 - 6 * NX) sts128(A_TAB + (tid + k * NX) * 16, 0, 0, 0, 0);
    bar_sync(3, NX + 96);
    STAMP(12);
    const char* xin = (const char*)(p.s->x + cta * G * 24);
    uint32_t pk[11];
    const uint32_t rot = (lane + cta) & 31;
    auto poll_a = [&]() {
#pragma unroll
      for (int k = 0; k < 11; k++) pk[k] = ldg_poll(xin + (j0 + JS * k) * FS + rot * 4);
    };
    uint32_t xs = ~0u; uint2 xv;
    const uint32_t t0 = j0 * FS + 128 + rot * 8, tx = lane ? tga : tgh;
    const uint32_t h1 = (cta & 31) * 4 + 4 + 62 * 258;
    int spin = 0;
    auto copy_b = [&]() {
      const uint32_t o = (j0 + JS * (lane >> 4)) * FS + 128 + (lane & 15) * 16;
#pragma unroll
      for (int k = 0; k < 6; k++) if (k < 5 || lane < 16)
        asm volatile("cp.async.cg.shared.global.L2::cache_hint [%0], [%1], 16, %2;" :: "r"(A_IN + o + k * 2 * JS * FS), "l"(xin + o + k * 2 * JS * FS), "l"(pol_first()) : "memory");
    };
    {
      const int blk = (wid >> 2) + 1;
      mbar_wait(BAR_T + blk * 8, 0);
      if (wid == 8) STAMP(22);
      mma(a0, 0, blk); mma(a1, 1, blk);
      asm volatile("wgmma.wait_group.sync.aligned 1;" ::: "memory"); fence_regs(a0);
      epi(a0, 0, blk);
      bar_arrive(8, NX + 32);
      if (PG < 0) poll_a();
      wg_wait0(); fence_regs(a1);
      bar_sync(13 + (wid >> 2), 128);
      epi(a1, 1, blk);
      p_check(blk);
      if (PG >= 0) { mbar_wait(BAR_T + PG * 8, 0); poll_a(); }
      if (wid == 8) STAMP(24);
    }
    {
      {
        for (;;) {
          uint32_t mh = 0, bad = 0;
#pragma unroll
          for (int k = 0; k < 11; k++) { pk[k] ^= tx; mh = max(mh, pk[k]); bad |= pk[k]; }
          if (!__any_sync(~0u, bad & (lane ? 0xFC00FC00u : 0xFC000000u))) {
            if (__shfl_sync(~0u, mh, 0) > h1) {
              uint32_t base = 0;
#pragma unroll
              for (int k = 0; k < 11; k++) {
                const uint32_t c = (max(__shfl_sync(~0u, pk[k], 0), h1) - h1) / 258;
                if (lane - base < c) xs = (j0 + JS * k) * 32 + lane - base;
                base += c;
              }
              if (base > 31) { sts32(A_MISC, 1); xs = ~0u; }
              if (xs != ~0u) xv = ldg_poll2(p.s->xe + cta * G * 32 + xs);
              __syncwarp();
            }
            break;
          }
          if (++spin > 2000000) __trap();
          poll_a();
        }
        STAMP(14); if (wid == 8) STAMP(25);
        uint32_t r0[11], r1[11];
#pragma unroll
        for (int k = 0; k < 11; k++) {
          if (lane == 0) pk[k] = (512 + rot) * 0x10001u;
          r0[k] = atoms_add(A_CNT + (pk[k] & 0xFFFF) * 4, 2);
          r1[k] = atoms_add(A_CNT + (pk[k] >> 16) * 4, 2);
        }
#pragma unroll
        for (int k = 0; k < 11; k++) { sts16(min(r0[k], A_IN - 2), t0 + JS * k * FS); sts16(min(r1[k], A_IN - 2), t0 + JS * k * FS + 4); }
        if (wid == 8) STAMP(26);
      }
    }
    if (tid == 0) { asm volatile("cp.async.bulk.wait_group.read 0;" ::: "memory"); if (CBH) mbar_wait(BAR_T + 40, 0); mbar_arrive(BAR_X); }
    __syncwarp();
    mbar_wait(BAR_X, 0);
    copy_b();
    STAMP(4);
    if (xs != ~0u) {
      for (int i = 0; (((xv.x ^ tgb) >> 29) | ((xv.y >> 9) ^ (ep & 0x7FFFFF))) && i < 2000000; i++) xv = ldg_poll2(p.s->xe + cta * G * 32 + xs);
      const uint32_t t = (xs >> 5) * FS + 4 + (xs & 31) * 4;
      sts16(min(atoms_add(A_CNT + (xv.y & 511) * 4, 2), A_IN - 2), t);
      sts32(A_IN + t, xv.x);
    }
    __syncwarp();
    bar_sync(4, NX);
    STAMP(5);
    {
      const uint32_t dg = (lds32(acnt) - (A_TAB + tid * (CAP * 2))) >> 1;
      const uint32_t dr = atoms_add(A_DH + min(dg, 63u) * 4, 1);
      bar_sync(5, NX);
      uint32_t hb, ha; lds64(hb, ha, A_DH + (62 - 2 * lane) * 4);
      uint32_t inc = ha + hb;
#pragma unroll
      for (int o = 1; o < 32; o <<= 1) { const uint32_t y = __shfl_up_sync(~0u, inc, o); if (lane >= o) inc += y; }
      const uint32_t idx = 63 - min(dg, 63u);
      const uint32_t e2 = __shfl_sync(~0u, (inc - hb) | ((inc - hb - ha) << 16), idx >> 1);
      const uint32_t pos = ((idx & 1) ? (e2 & 0xFFFF) : (e2 >> 16)) + dr;
      sts16(A_ROWS + pos * 2, tid);
      if (!(pos & 7)) sts32(A_LEN + (pos >> 1), max(1u, (dg + 1) >> 1));
      if (dg > CAP) sts32(A_MISC, 1);
    }
    STAMP(6);
    if (tid == 0) sts32(A_IN, 0xFFFF);
    for (;;) {
      asm volatile("cp.async.wait_all;" ::: "memory");
      __syncwarp();
      uint32_t bad = 0;
#pragma unroll
      for (int k = 0; k < 11; k++) { uint32_t x, y; lds64(x, y, A_IN + t0 + JS * k * FS); bad |= (x ^ tgb) | (y ^ tgb); }
      if (!__any_sync(~0u, bad >> 29) || ++spin > 2000000) break;
      copy_b();
    }
    STAMP(7);
  }
  if (wid == 15) {
    bar_arrive(11, NT);
    if (lane == 0) { bulk_commit(); asm volatile("cp.async.bulk.wait_group 0;" ::: "memory"); }
    __syncwarp();
    if (lane < NREP) asm volatile("red.relaxed.gpu.global.add.u32 [%0], 1;" :: "l"(p.s->cnt + lane * 32) : "memory");
    if (lane == 0) {
      STAMP(19);
      const uint32_t nbe = (p.E / G) & ~15u;
#pragma unroll 1
      for (int i = 0; i < PFA; i++)
        if (nbe) asm volatile("cp.async.bulk.prefetch.L2.global [%0], %1;" :: "l"((const char*)p.ea + (size_t)(i * G + cta) * nbe), "r"(nbe) : "memory");
      uint32_t c; int spin = 0;
      do { asm volatile("ld.acquire.gpu.global.u32 %0, [%1];" : "=r"(c) : "l"(p.s->cnt + (cta % NREP) * 32) : "memory"); } while ((int)(c - ep * G) < 0 && ++spin < 20000000);
      mbar_arrive(BAR_Q);
      STAMP(20);
    }
    __syncwarp();
  }
  uint32_t W3[16], PB[16], WX[8];
#pragma unroll
  for (int k = 0; k < 4; k++) ldsm4t(W3[4 * k], W3[4 * k + 1], W3[4 * k + 2], W3[4 * k + 3], A_W3 + (lane & 15) * 128 + ((((lane >> 4) + 2 * k) ^ (lane & 7)) << 4));
#pragma unroll
  for (int j = 0; j < 8; j++) WX[j] = lds32(A_WD + 128 + j * 16 + q * 4);
  uint32_t A2[4];
  const uint32_t ring = A_RING + wid * 5120;
  const int oc = lane >> 3;
  const int r7 = lane & 7, ro = r7 >> 1, ri = 2 * (oc & 1) + (r7 & 1);
  uint64_t qp0 = (uint64_t)p.s->q + ((r7 ^ (2 * oc)) << 4), qp1 = qp0 ^ 16, epp = (uint64_t)p.ea + (((lane ^ oc) & 1) << 4) - (tgb >> 11);
  uint32_t dq = ring + oc * 512 + r7 * 16, de = ring + 2048 + ((lane * 16) ^ ((oc >> 1) * 64));
  uint32_t rq = ring + (4 * ro + ri) * 128 + (((oc >> 1) ^ r7) << 4), re = ring + 2048 + ro * 128 + ((ri ^ (2 * (ro >> 1))) << 5) + ((((oc >> 1) ^ ro) & 1) << 4);
  A2[0] = (g8 >> 1) == q ? ((g8 & 1) ? 0x3C000000u : 0x3C00u) : 0;
  A2[0] += lds32(A_MISC + 8); A2[1] = A2[0] + lds32(A_MISC + 8);
  asm volatile("" : "+l"(qp0), "+l"(qp1), "+l"(epp), "+r"(dq), "+r"(de), "+r"(rq), "+r"(re));
  if (wid < 15) { bar_sync(11, NT); if (wid == 14) bar_arrive(12, 64); } else bar_sync(12, 64);
  STAMP(13);
  if (lds32(A_MISC)) { sts32(A_MISC + 12, dq ^ de ^ rq ^ re ^ (uint32_t)qp0 ^ (uint32_t)qp1 ^ (uint32_t)(epp ^ (epp >> 32)) ^ A2[1]); __syncthreads(); slow_path(p); return; }

  uint32_t MS[8], acc[16], m[16], A1[4], OP, TA, D = 0, U = 0, tt, rec, sl;
  uint64_t pol; asm("createpolicy.fractional.L2::evict_first.b64 %0, " EFR ";" : "=l"(pol));
  if (EKEEP) asm("createpolicy.range.global.L2::" EPOL ".L2::evict_first.b64 %0, [%1], %2, %3;" : "=l"(pol) : "l"(p.ea), "r"(p.E * EKEEP), "r"(p.E * 32));
  const uint32_t zr = p.force_slow;
  uint32_t nd3, mk, ln, gl = 10, gc = 0;
  auto lane_id = []() { uint32_t l; asm volatile("mov.u32 %0, %%laneid;" : "=r"(l)); return l; };
  auto slot_node = [&](uint32_t l) { return __shfl_sync(~0u, nd3, ((l >> 2) & 6) | ((l >> 1) & 1)); };
  auto lswitch = [&]() {
    const uint32_t l = lane_id();
    TA = A_TAB + (ln ? (slot_node(l) >> gl) & 1023 : 384) * (CAP * 2) + ((l >> 1) & 2);
    if (ln) mk |= 8u << (ln & 255);
    else if (atoms_incp(A_MISC + 4, l == 0) == 31) {
      proxy_fence();
      mbar_expect(BAR_U, 16384);
      tma_load(A_TAB, tmb + TM_WH, 0, BAR_U); tma_load(A_TAB + 8192, tmb + TM_WH, 64, BAR_U);
    }
    __syncwarp();
    ln >>= 8; gl += 10;
  };
  auto pswitch = [&]() {
    const uint32_t l = lane_id(), nd = (nd3 >> gc) & 1023;
    const uint32_t a = ((l & 8) ? A_WD2 + (l & 7) * 144 : A_PT + nd * 128 + ((nd & 7) << 4)) ^ (l & 16);
#pragma unroll
    for (int k = 0; k < 4; k++) ldsm4t(PB[4 * k], PB[4 * k + 1], PB[4 * k + 2], PB[4 * k + 3], a ^ (k << 5));
    OP = lds16(A_POSH + __shfl_sync(~0u, nd, l >> 2) * 8 + (l & 3) * 2) * 0x10001;
  };
  auto flush = [&](bool keep) {
    const uint32_t l = lane_id(), nd = (nd3 >> gc) & 1023, a = A_PT + nd * 128 + (((l >> 3) ^ (nd & 7)) << 4);
    uint32_t c0_ = 0, c1_ = 0;
#pragma unroll
    for (int k = 0; k < 4; k++) hmma(c0_, c1_, m + 4 * k, WX[2 * k], WX[2 * k + 1]);
    U = hfma(__byte_perm(c0_, c1_, 0x5410), D, U);
    uint32_t ov = U;
#pragma unroll
    for (int j = 0; j < 8; j++) { ov = hfma(MS[j], 0, ov); MS[j] = h2b(MS[j]); }
    stsm4(a, MS[0], MS[1], MS[2], MS[3]); stsm4(a ^ 64, MS[4], MS[5], MS[6], MS[7]);
    const uint32_t pa = A_POSB + __shfl_sync(~0u, nd, l >> 2) * 6 + (l & 3) * 2;
    const float2 f = __half22float2(*(const __half2*)&U);
    sts16p(pa, pack_bf16(fmaf(f.x + f.y, __uint_as_float(lds32(A_MISC + 12)), bf_lo(lds16(pa))), 0.f), (l & 3) < 3);
    sts32p(A_MISC + 8, 1, (((ov & 0x7FFF7FFFu) + 0x04000400u) & 0x80008000u) != 0);
    if (!keep) {
      U = 0; D = 0;
#pragma unroll
      for (int j = 0; j < 8; j++) MS[j] = 0;
    }
  };
  auto look = [&]() {
    asm volatile("ld.volatile.shared.u16 %0, [%1];" : "=r"(tt) : "r"(TA) : "memory"); TA += 4;
    asm volatile("ld.volatile.shared.u32 %0, [%1];" : "=r"(rec) : "r"(A_IN + tt) : "memory");
    tt = __umulhi(tt, 11184811u) * p.EPC + (rec >> 16); rec &= 0xFFFF;
    if (ABL & 1) tt = (tt & 0x1FFFF) + 65536;
  };
  auto issue = [&](uint32_t st, uint32_t rec, uint32_t tt, uint32_t mk) {
#pragma unroll
    for (int i = 0; i < 4; i++)
      if (ABL & 2) asm volatile("{.reg .b64 a; .reg .pred p, l; setp.eq.u32 p, %2, 0xFFFF; setp.ge.u32 l, %3, 8; mad.wide.u32 a, %2, 128, %1;\n @l cp.async.cg.shared.global [%0], [a], 16, p;}"
        :: "r"(dq + i * 128 + st), "l"((i & 1) ? qp1 : qp0), "r"(__shfl_sync(~0u, rec, 2 * i, 8)), "r"(zr) : "memory");
      else asm volatile("{.reg .b64 a; .reg .pred p; setp.eq.u32 p, %2, 0xFFFF; mad.wide.u32 a, %2, 128, %1;\n cp.async.cg.shared.global [%0], [a], 16, p;}"
        :: "r"(dq + i * 128 + st), "l"((i & 1) ? qp1 : qp0), "r"(__shfl_sync(~0u, rec, 2 * i, 8)) : "memory");
    asm volatile("{.reg .b64 a; .reg .pred p, l; setp.eq.u32 p, %3, 0xFFFF; setp.ge.u32 l, %4, 8; mad.wide.u32 a, %2, 32, %1;\n @l cp.async.cg.shared.global.L2::cache_hint [%0], [a], 16, p, %5;}"
      :: "r"(de + st), "l"(epp), "r"(tt), "r"(rec), "r"((ABL & 2) ? zr : mk), "l"(pol) : "memory");
    asm volatile("cp.async.commit_group;" ::: "memory");
  };
  auto step = [&](uint32_t st) {
    if ((mk & 9) || mk < 8) {
      if (mk & 1) { flush(false); gc += 10; pswitch(); }
      if (mk & 8) lswitch();
      if (mk < 8) {
        const uint32_t l = lane_id(); int cta; asm volatile("mov.u32 %0, %%ctaid.x;" : "=r"(cta));
        rec = ((slot_node(l) >> (mk < 4 ? 20 : (l & 4) ? 10 : 0)) & 1023) + cta * p.NPC;
        if (rec >= p.N || (mk < 4 && (l & 4))) rec = 0xFFFF;
        qp0 = (uint64_t)p.h + (qp0 & 127); qp1 = qp0 ^ 16;
      }
    }
    asm volatile("cp.async.wait_group 1;" ::: "memory");
    __syncwarp();
    uint32_t E[4];
    ldsm4(E, re + st);
#pragma unroll
    for (int k = 0; k < 4; k++) ldsm4(acc + 4 * k, (rq ^ (k * 32)) + st);
    issue(st, rec, tt, mk);
    look();
    if (ABL & 4) { U ^= (E[0] ^ acc[0] ^ acc[4] ^ acc[8] ^ acc[12]) & zr; mk >>= 1; return; }
#pragma unroll
    for (int i = 0; i < 4; i++) A1[i] = b2h(E[i]);
    const uint32_t Sa = acc[0] + acc[2] * 4 + acc[4] * 16 + acc[6] * 64, Sb = acc[1] + acc[3] * 4 + acc[5] * 16 + acc[7] * 64;
    mk >>= 1;
    const uint32_t Dp = D;
    D = hsub(OP, __byte_perm(Sa, Sb, 0x6420));
    const __half2 d = *(const __half2*)&D, x = __hmul2(d, d), y = __hmul2(__high2half2(d), __high2half2(d));
    A2[2] = *(const uint32_t*)&x; A2[3] = *(const uint32_t*)&y;
    uint32_t c0_ = 0, c1_;
#pragma unroll
    for (int k = 0; k < 4; k++) {
#pragma unroll
      for (int j = 2 * k; j < 2 * k + 2; j++) { hmma(acc[2 * j], acc[2 * j + 1], A1, W3[2 * j], W3[2 * j + 1]); hmma(acc[2 * j], acc[2 * j + 1], A2, PB[2 * j], PB[2 * j + 1]); }
      if (k == 0) c1_ = acc[VAR] & zr;
      hmma(c0_, c1_, m + 4 * k, WX[2 * k], WX[2 * k + 1]);
#pragma unroll
      for (int i = 0; i < 4; i++) { m[4 * k + i] = hsilu(acc[4 * k + i]); MS[2 * k + (i >> 1)] = hadd(MS[2 * k + (i >> 1)], m[4 * k + i]); }
    }
    U = hfma(__byte_perm(c0_, c1_, 0x5410), Dp, U);
  };
#pragma unroll
  for (int i = 0; i < 16; i++) m[i] = 0;
#pragma unroll
  for (int j = 0; j < 8; j++) MS[j] = 0;
  { const uint32_t sc = p.sched[wid], g0 = sc & 63, g1 = (sc >> 6) & 63, g2 = sc >> 12;
    TA = A_TAB + lds16(A_ROWS + g0 * 16 + oc * 4 + (lane & 2)) * (CAP * 2) + ((lane >> 1) & 2);
    nd3 = lds16(A_ROWS + g0 * 16 + r7 * 2) | (lds16(A_ROWS + g1 * 16 + r7 * 2) << 10) | (lds16(A_ROWS + g2 * 16 + r7 * 2) << 20);
    ln = __shfl_sync(~0u, lds32(A_LEN + g0 * 4) | (lds32(A_LEN + g1 * 4) << 8) | (lds32(A_LEN + g2 * 4) << 16), 0);
    mk = 4u << (ln & 255); ln >>= 8;
    look();
    uint32_t ra = 0, ta = 0, rb = 0, tb = 0;
#pragma unroll 1
    for (int k = 0; k < 2; k++) { if (mk & 8) lswitch(); ra = rb; ta = tb; rb = rec; tb = tt; look(); mk >>= 1; }
    mbar_wait(BAR_Q, 0);
    STAMP(8);
    issue(0, ra, ta, 8);
    pswitch();
    issue(2560, rb, tb, 8);
  }
#pragma unroll 1
  for (;;) {
    step(0); if (mk == 1) { sl = 0; break; }
    step(2560); if (mk == 1) { sl = 2560; break; }
  }
  flush(true);
  STAMP(9);
  {
    int cta; asm volatile("mov.u32 %0, %%ctaid.x;" : "=r"(cta));
    const uint32_t l = lane_id(), node0 = cta * p.NPC; const int nloc = min(p.NPC, p.N - (int)node0);
    constexpr uint64_t dW = DHI | (A_TAB >> 4);
    float y1[32], y2[32];
    uint32_t H[16], po[3];
    auto rows = [&](uint32_t* v, uint32_t nd) {
      const uint32_t a = A_PT + nd * 128 + (((l >> 4) ^ (nd & 7)) << 4);
#pragma unroll
      for (int k = 0; k < 4; k++) ldsm4(v + 4 * k, a ^ (k << 5));
    };
    asm volatile("cp.async.wait_group 1;" ::: "memory");
    __syncwarp();
    rows(m, (nd3 >> ((l & 8) ? 10 : 0)) & 1023);
#pragma unroll
    for (int k = 0; k < 4; k++) ldsm4(H + 4 * k, (rq ^ (k * 32)) + (sl ^ 2560));
    mbar_wait(BAR_U, 0);
    STAMP(10);
    wg_fence();
    rs64<0>(y1, m, dW + 512); rs64<1>(y1, m + 4, dW + 640); rs64<1>(y1, m + 8, dW + 768); rs64<1>(y1, m + 12, dW + 896);
    rs64<1>(y1, H, dW); rs64<1>(y1, H + 4, dW + 128); rs64<1>(y1, H + 8, dW + 256); rs64<1>(y1, H + 12, dW + 384);
    wg_commit();
    { const uint32_t n0 = __shfl_sync(~0u, nd3, (l >> 2) & 6), n1 = __shfl_sync(~0u, nd3, ((l >> 2) & 6) | 1);
#pragma unroll
      for (int g = 0; g < 3; g++) po[g] = ((n0 >> (10 * g)) & 1023) | (((n1 >> (10 * g)) & 1023) << 16); }
    const uint64_t ob = (uint64_t)(p.out + (size_t)node0 * 64) + (((l & 7) ^ ((l >> 2) & 6)) << 4);
    wg_wait0(); fence_regs(y1);
    rows(m, nd3 >> 20);
    auto fin = [&](uint32_t x, float a, float b) { return badd(x, pack_bf16(silu(a), silu(b))); };
    auto put = [&](uint32_t a, uint32_t nn) {
      uint32_t v[8]; lds128(v, a); lds128(v + 4, a + 128);
#pragma unroll
      for (int i = 0; i < 2; i++)
        asm volatile("{.reg .pred p; .reg .b64 a; setp.lt.s32 p, %0, %1; mad.wide.u32 a, %0, 128, %2; @p st.global.v4.u32 [a], {%3,%4,%5,%6};}"
          :: "r"(i ? nn >> 16 : nn & 0xFFFF), "r"(nloc), "l"(ob ^ (i << 4)), "r"(v[4 * i]), "r"(v[4 * i + 1]), "r"(v[4 * i + 2]), "r"(v[4 * i + 3]) : "memory");
    };
#pragma unroll
    for (int j = 0; j < 4; j++) H[j] = fin(H[j], y1[2 * j], y1[2 * j + 1]);
    wg_fence();
    rs64<0>(y2, m, dW + 512); rs64<1>(y2, m + 4, dW + 640); rs64<1>(y2, m + 8, dW + 768); rs64<1>(y2, m + 12, dW + 896);
    wg_commit();
#pragma unroll
    for (int j = 4; j < 10; j++) H[j] = fin(H[j], y1[2 * j], y1[2 * j + 1]);
    asm volatile("cp.async.wait_group 0;" ::: "memory");
    __syncwarp();
    wg_wait0(); fence_regs(y2);
#pragma unroll
    for (int k = 0; k < 4; k++) ldsm4(m + 4 * k, (rq ^ (k * 32)) + sl);
#pragma unroll
    for (int j = 10; j < 13; j++) H[j] = fin(H[j], y1[2 * j], y1[2 * j + 1]);
    wg_fence();
    rs64<1>(y2, m, dW); rs64<1>(y2, m + 4, dW + 128); rs64<1>(y2, m + 8, dW + 256); rs64<1>(y2, m + 12, dW + 384);
    wg_commit();
#pragma unroll
    for (int j = 13; j < 16; j++) H[j] = fin(H[j], y1[2 * j], y1[2 * j + 1]);
#pragma unroll
    for (int k = 0; k < 4; k++) stsm4((rq ^ (k * 32)) + (sl ^ 2560), H[4 * k], H[4 * k + 1], H[4 * k + 2], H[4 * k + 3]);
    __syncwarp();
    put(dq + (sl ^ 2560), po[0]); put(dq + 256 + (sl ^ 2560), po[1]);
    wg_wait0(); fence_regs(y2);
#pragma unroll
    for (int j = 0; j < 16; j += 2) m[j] = fin(m[j], y2[2 * j], y2[2 * j + 1]);
#pragma unroll
    for (int k = 0; k < 4; k++) stsm4((rq ^ (k * 32)) + sl, m[4 * k], m[4 * k + 1], m[4 * k + 2], m[4 * k + 3]);
    __syncwarp();
    put(dq + sl, po[2]);
    __syncthreads();
    if (!ABL && lds32(A_MISC + 8)) { slow_path(p); return; }
    uint16_t* op = p.out + (size_t)p.N * 64 + (size_t)node0 * 3 + threadIdx.x;
#pragma unroll
    for (int k = 0; k < 3; k++)
      asm volatile("{.reg .pred p; setp.lt.s32 p, %0, %1; @p st.global.u16 [%2], %3;}" :: "r"(threadIdx.x + k * NT), "r"(nloc * 3), "l"(op + k * NT), "h"((uint16_t)lds16(A_POSB + (threadIdx.x + k * NT) * 2)) : "memory");
  }
  STAMP(11);
}

}

typedef CUresult (*EncodeFn)(CUtensorMap*, CUtensorMapDataType, cuuint32_t, void*, const cuuint64_t*, const cuuint64_t*, const cuuint32_t*, const cuuint32_t*,
                             CUtensorMapInterleave, CUtensorMapSwizzle, CUtensorMapL2promotion, CUtensorMapFloatOOBfill);

extern "C" void kernel_launch(void* const* d_in, const int* in_sizes, int n_in, void* d_out, int out_size) {
  Params p; Maps maps;
  p.h = (const uint16_t*)d_in[0]; p.pos = (const uint16_t*)d_in[1]; p.ea = (const uint16_t*)d_in[2];
  p.src = (const int*)d_in[3]; p.dst = (const int*)d_in[4];
  p.we = (const uint16_t*)d_in[5]; p.wx = (const uint16_t*)d_in[6]; p.wh = (const uint16_t*)d_in[7];
  p.out = (uint16_t*)d_out;
  p.N = in_sizes[0] / 64; p.E = in_sizes[3];
  p.NPC = (p.N + G - 1) / G;
  p.EPC = ((p.E + G * 4 - 1) / (G * 4)) * 4;
  p.magic = (uint32_t)((1ull << 32) / (uint64_t)p.NPC) + 1;
  const uint32_t sched[16] = {0x2d504, 0x29783, 0x2b8c2, 0x2a38b, 0x28448, 0x1f68c, 0x185d3, 0x22747, 0x2558a, 0x2e345, 0x2f9c0, 0x2c901, 0x26646, 0x216c9, 0x1c550, 0x2048f};
  for (int i = 0; i < 16; i++) p.sched[i] = sched[i];
  uint64_t al = (uint64_t)d_out;
  for (int i = 0; i < 8; i++) if (i != 1) al |= (uint64_t)d_in[i];
  p.force_slow = (al & 127) || (p.E & 3) || p.NPC > 384 || p.NPC < 2 || p.EPC > 6144;
  cudaGetSymbolAddress((void**)&p.s, g_s);
  void* fn = nullptr; cudaDriverEntryPointQueryResult qr;
  cudaGetDriverEntryPoint("cuTensorMapEncodeTiled", &fn, cudaEnableDefault, &qr);
  auto mk = [&](CUtensorMap* tm, void* base, int rows, int box) {
    const cuuint64_t dim[2] = {64, (cuuint64_t)rows}, str[1] = {128}; const cuuint32_t bx[2] = {64, (cuuint32_t)box}, es[2] = {1, 1};
    ((EncodeFn)fn)(tm, CU_TENSOR_MAP_DATA_TYPE_BFLOAT16, 2, base, dim, str, bx, es, CU_TENSOR_MAP_INTERLEAVE_NONE, CU_TENSOR_MAP_SWIZZLE_128B,
                   CU_TENSOR_MAP_L2_PROMOTION_NONE, CU_TENSOR_MAP_FLOAT_OOB_FILL_NONE);
  };
  mk(&maps.m[TM_H / 128], d_in[0], p.N, 64); mk(&maps.m[TM_WE / 128], d_in[5], 145, 64); mk(&maps.m[TM_WH / 128], d_in[7], 128, 64);
  mk(&maps.m[TM_Q / 128], p.s->q, p.N, 64); mk(&maps.m[TM_O / 128], d_out, p.N, 64); mk(&maps.m[TM_O2 / 128], d_out, p.N, (p.NPC & 63) ? (p.NPC & 63) : 64);
  mk(&maps.m[TM_W3 / 128], d_in[5], 145, 16);
  for (int k = 0; k < 2; k++) {
    const cuuint64_t dim[2] = {(cuuint64_t)G * (192 >> k), (cuuint64_t)G}, str[1] = {(cuuint64_t)G * FS}; const cuuint32_t bx[2] = {64, G}, es[2] = {1, 1};
    ((EncodeFn)fn)(&maps.m[TM_XA / 128 + k], k ? CU_TENSOR_MAP_DATA_TYPE_UINT32 : CU_TENSOR_MAP_DATA_TYPE_UINT16, 2, p.s->x, dim, str, bx, es, CU_TENSOR_MAP_INTERLEAVE_NONE,
                   CU_TENSOR_MAP_SWIZZLE_NONE, CU_TENSOR_MAP_L2_PROMOTION_NONE, CU_TENSOR_MAP_FLOAT_OOB_FILL_NONE);
  }
  cudaFuncSetAttribute(egnn_kernel, cudaFuncAttributeMaxDynamicSharedMemorySize, SMEM);
  egnn_kernel<<<G, NT, SMEM>>>(p, maps);
}
```

```cpp
#include <cuda_runtime.h>
#include <cuda_bf16.h>
#include <cuda_fp16.h>
#include <cuda.h>
#include <stdint.h>

#define PFA 6
#define HPF 99
#define CHK 8192
#define EPOL "evict_normal"
#define XPOL 2
#define ORD 0
#define WIN 6
#define RF 3
#define PFT 400
#define QHOLD 1
#define PSW 1
#define TLBW 0
#define BL 0
#define CBH 0
#define UNR 1
#define DEF 2
namespace {

constexpr int G = 132;
constexpr int NT = 512;
constexpr int CAP = 48;
constexpr int FS = 384;
constexpr int BS = 1152;
constexpr uint32_t sb = 1024;

constexpr uint32_t A_RING = sb;
constexpr uint32_t A_PT = A_RING + 16 * 5120;
constexpr uint32_t A_W3 = A_PT + 49152;
constexpr uint32_t A_TAB = A_W3 + 2048;
constexpr uint32_t A_IN = A_TAB + 37888;
constexpr uint32_t A_WD = A_IN + G * FS + 512;
constexpr uint32_t A_WD2 = A_WD + 256;
constexpr uint32_t A_BAR = A_WD2 + 1024;
constexpr uint32_t A_MISC = A_BAR + 160;
constexpr uint32_t A_DH = A_MISC + 16;
constexpr uint32_t A_CNT = A_DH + 256;
constexpr uint32_t A_POSH = A_CNT + 2176;
constexpr uint32_t A_POSB = A_POSH + 3072;
constexpr uint32_t A_ROWS = A_POSB + 2304;
constexpr uint32_t A_LEN = A_ROWS + 768;
constexpr uint32_t A_END = A_LEN + 192;
constexpr uint32_t A_XC = A_TAB + 385 * CAP * 2, A_TRASH = A_XC + 144;
constexpr uint32_t A_E3 = A_IN + G / 4 * BS;
constexpr int SMEM = A_END - sb;
static_assert(SMEM <= 232448 && A_TAB % 1024 == 0 && A_IN % 1024 == 0 && A_PT % 1024 == 0 && A_WD2 % 128 == 0, "smem");
constexpr int NX = 384, CH = NX * 16;
constexpr uint32_t A_QS = A_RING, A_W = A_QS + 49152, A_SA = A_IN, A_SB = A_SA + (G + 1) * 128, A_SRC = A_TAB;
__host__ __device__ constexpr uint32_t a_dst(int k) { return k < 2 ? A_W + 16384 + k * CH : A_SRC + (k + 2) * CH; }
static_assert(a_dst(1) + CH <= A_PT && a_dst(3) + CH <= A_IN && A_SB + (G + 1) * 256 <= A_WD, "staging");
constexpr uint32_t BAR_C = A_BAR, BAR_T = BAR_C + 64, BAR_W = A_BAR + 112, BAR_U = A_BAR + 120, BAR_Q = A_BAR + 128, BAR_X = A_BAR + 136, BAR_A = A_BAR + 144;

#define ABL 0
#define JSV 12
#define ESZ ""
#define VAR 177
#define STAT 1
#define PFB 0
#define PFR 3
#define EFR "1.0"
#define EKEEP 6
#define QH 5
#define QH0 0
#define PG -1
#define EXR 0
#define RK 1
#define YP 0
#define NEST 0
#define HK 0
#define DESC 0
#define LK 0
#define NREPV 8
#define PFD 0
#define EH 1
constexpr int NREP = NREPV;
struct Scratch {
  uint4 q[(G * 384 + 64) * 8];
  uint4 x[G * G * 24];
  uint2 xe[G * G * 32];
  uint32_t ep[G * 32];
  uint32_t cnt[NREP * 32];
};
__device__ __align__(256) Scratch g_s;
#define STAMP(k)

struct Maps { CUtensorMap m[9]; };
constexpr int TM_H = 0, TM_WE = 128, TM_WH = 256, TM_Q = 384, TM_O = 512, TM_O2 = 640, TM_XA = 768, TM_XB = 896, TM_W3 = 1024;
struct Params {
  const int* dst; const int* src; int E, EPC, force_slow, NPC; Scratch* s; int N; uint32_t magic;
  const uint16_t* h; const uint16_t* pos; const uint16_t* ea; const uint16_t* we; const uint16_t* wx; const uint16_t* wh; uint16_t* out;
  uint32_t EPC4, sched[16];
};

#define R32(d) "+f"(d[0]),"+f"(d[1]),"+f"(d[2]),"+f"(d[3]),"+f"(d[4]),"+f"(d[5]),"+f"(d[6]),"+f"(d[7]),"+f"(d[8]),"+f"(d[9]),"+f"(d[10]),"+f"(d[11]),"+f"(d[12]),"+f"(d[13]),"+f"(d[14]),"+f"(d[15]),"+f"(d[16]),"+f"(d[17]),"+f"(d[18]),"+f"(d[19]),"+f"(d[20]),"+f"(d[21]),"+f"(d[22]),"+f"(d[23]),"+f"(d[24]),"+f"(d[25]),"+f"(d[26]),"+f"(d[27]),"+f"(d[28]),"+f"(d[29]),"+f"(d[30]),"+f"(d[31])
#define S32 "{%0,%1,%2,%3,%4,%5,%6,%7,%8,%9,%10,%11,%12,%13,%14,%15,%16,%17,%18,%19,%20,%21,%22,%23,%24,%25,%26,%27,%28,%29,%30,%31}"
#define R16(d) "+f"(d[0]),"+f"(d[1]),"+f"(d[2]),"+f"(d[3]),"+f"(d[4]),"+f"(d[5]),"+f"(d[6]),"+f"(d[7]),"+f"(d[8]),"+f"(d[9]),"+f"(d[10]),"+f"(d[11]),"+f"(d[12]),"+f"(d[13]),"+f"(d[14]),"+f"(d[15])
#define S16 "{%0,%1,%2,%3,%4,%5,%6,%7,%8,%9,%10,%11,%12,%13,%14,%15}"
#define DI __device__ __forceinline__

constexpr uint64_t DHI = (64ull << 32) | (1ull << 62);
template<int SD> DI void ss64(float (&d)[32], uint64_t da, uint64_t db) {
  asm volatile("wgmma.mma_async.sync.aligned.m64n64k16.f32.bf16.bf16 " S32 ", %32, %33, %34, 1, 1, 0, 1;" : R32(d) : "l"(da), "l"(db), "n"(SD)); }
template<int SD> DI void rs64(float (&d)[32], const uint32_t* a, uint64_t db) {
  asm volatile("wgmma.mma_async.sync.aligned.m64n64k16.f32.bf16.bf16 " S32 ", {%32,%33,%34,%35}, %36, %37, 1, 1, 1;" : R32(d) : "r"(a[0]), "r"(a[1]), "r"(a[2]), "r"(a[3]), "l"(db), "n"(SD)); }
DI void wg_fence() { asm volatile("wgmma.fence.sync.aligned;" ::: "memory"); }
DI void wg_commit() { asm volatile("wgmma.commit_group.sync.aligned;" ::: "memory"); }
DI void wg_wait0() { asm volatile("wgmma.wait_group.sync.aligned 0;" ::: "memory"); }
DI void fence_regs(float (&d)[32]) { asm volatile("" : R32(d) :: "memory"); }
DI void fence_regs(float (&d)[16]) { asm volatile("" : R16(d) :: "memory"); }
DI void proxy_fence() { asm volatile("fence.proxy.async.shared::cta;" ::: "memory"); }
DI void hmma(uint32_t& d0, uint32_t& d1, const uint32_t* a, uint32_t b0, uint32_t b1) {
  asm("mma.sync.aligned.m16n8k16.row.col.f16.f16.f16.f16 {%0,%1}, {%2,%3,%4,%5}, {%6,%7}, {%0,%1};" : "+r"(d0), "+r"(d1) : "r"(a[0]), "r"(a[1]), "r"(a[2]), "r"(a[3]), "r"(b0), "r"(b1)); }
DI uint64_t pol_first() { uint64_t r; asm("createpolicy.fractional.L2::evict_first.b64 %0, 1.0;" : "=l"(r)); return r; }
DI float tanh_ap(float x) { float y; asm("tanh.approx.f32 %0, %1;" : "=f"(y) : "f"(x)); return y; }
DI float silu(float x) { const float y = 0.5f * x; return fmaf(y, tanh_ap(y), y); }
DI uint32_t pack_bf16(float lo, float hi) { uint32_t r; asm("cvt.rn.bf16x2.f32 %0, %1, %2;" : "=r"(r) : "f"(hi), "f"(lo)); return r; }
DI uint32_t pack_f16(float lo, float hi) { uint32_t r; asm("cvt.rn.f16x2.f32 %0, %1, %2;" : "=r"(r) : "f"(hi), "f"(lo)); return r; }
DI float bf_lo(uint32_t v) { return __uint_as_float(v << 16); }
DI float bf_hi(uint32_t v) { return __uint_as_float(v & 0xFFFF0000u); }
DI uint32_t b2h(uint32_t v) { return pack_f16(bf_lo(v), bf_hi(v)); }
DI uint32_t h2b(uint32_t v) { const float2 f = __half22float2(*(const __half2*)&v); return pack_bf16(f.x, f.y); }
DI uint32_t hadd(uint32_t a, uint32_t b) { uint32_t r; asm("add.rn.f16x2 %0, %1, %2;" : "=r"(r) : "r"(a), "r"(b)); return r; }
DI uint32_t hsub(uint32_t a, uint32_t b) { uint32_t r; asm("sub.rn.f16x2 %0, %1, %2;" : "=r"(r) : "r"(a), "r"(b)); return r; }
DI uint32_t hfma(uint32_t a, uint32_t b, uint32_t c) { uint32_t r; asm("fma.rn.f16x2 %0, %1, %2, %3;" : "=r"(r) : "r"(a), "r"(b), "r"(c)); return r; }
DI uint32_t hsilu(uint32_t y) { uint32_t t; asm("tanh.approx.f16x2 %0, %1;" : "=r"(t) : "r"(y)); return hfma(y, t, y); }
DI uint32_t badd(uint32_t a, uint32_t b) { uint32_t r; asm("add.rn.bf16x2 %0, %1, %2;" : "=r"(r) : "r"(a), "r"(b)); return r; }
DI uint32_t bhalf(uint32_t v) { uint32_t r; asm("mul.rn.bf16x2 %0, %1, %2;" : "=r"(r) : "r"(v), "r"(0x3F003F00u)); return r; }
DI uint32_t amax2(uint32_t mx, uint32_t v) { return __vmaxu2(mx, v & 0x7FFF7FFFu); }
DI uint32_t amax_warp(uint32_t mx) { return __reduce_max_sync(~0u, max(mx & 0xFFFF, mx >> 16)); }
DI void mbar_wait(uint32_t bar, uint32_t parity) {
  asm volatile("{.reg .pred p; .reg .u32 c; mov.u32 c, 0;\n"
    "LW_%=: mbarrier.try_wait.parity.shared::cta.b64 p, [%0], %1;\n"
    "@p bra.uni LD_%=;\n add.u32 c, c, 1; setp.lt.u32 p, c, 20000000;\n @p bra.uni LW_%=;\n LD_%=:}" :: "r"(bar), "r"(parity) : "memory");
}
DI void mbar_arrive(uint32_t bar) { asm volatile("mbarrier.arrive.shared::cta.b64 _, [%0];" :: "r"(bar) : "memory"); }
DI void bar_sync(int id, int n) { asm volatile("bar.sync %0, %1;" :: "r"(id), "r"(n) : "memory"); }
DI void bar_arrive(int id, int n) { asm volatile("bar.arrive %0, %1;" :: "r"(id), "r"(n) : "memory"); }
DI void sts128(uint32_t a, uint32_t x, uint32_t y, uint32_t z, uint32_t w) { asm volatile("st.shared.v4.u32 [%0], {%1,%2,%3,%4};" :: "r"(a), "r"(x), "r"(y), "r"(z), "r"(w) : "memory"); }
DI void sts64(uint32_t a, uint32_t x, uint32_t y) { asm volatile("st.shared.v2.u32 [%0], {%1,%2};" :: "r"(a), "r"(x), "r"(y) : "memory"); }
DI void sts32(uint32_t a, uint32_t x) { asm volatile("st.shared.u32 [%0], %1;" :: "r"(a), "r"(x) : "memory"); }
DI void sts16(uint32_t a, uint32_t x) { asm volatile("st.shared.u16 [%0], %1;" :: "r"(a), "h"((uint16_t)x) : "memory"); }
DI void sts32p(uint32_t a, uint32_t x, bool p) { asm volatile("{.reg .pred p; setp.ne.b32 p, %2, 0; @p st.shared.u32 [%0], %1;}" :: "r"(a), "r"(x), "r"((int)p) : "memory"); }
DI void sts16p(uint32_t a, uint32_t x, bool p) { asm volatile("{.reg .pred p; setp.ne.b32 p, %2, 0; @p st.shared.u16 [%0], %1;}" :: "r"(a), "h"((uint16_t)x), "r"((int)p) : "memory"); }
DI void lds128(uint32_t* v, uint32_t a) { asm volatile("ld.shared.v4.u32 {%0, %1, %2, %3}, [%4];" : "=r"(v[0]), "=r"(v[1]), "=r"(v[2]), "=r"(v[3]) : "r"(a) : "memory"); }
DI void lds64(uint32_t& x, uint32_t& y, uint32_t a) { asm volatile("ld.shared.v2.u32 {%0, %1}, [%2];" : "=r"(x), "=r"(y) : "r"(a) : "memory"); }
DI uint32_t lds32(uint32_t a) { uint32_t x; asm volatile("ld.shared.u32 %0, [%1];" : "=r"(x) : "r"(a) : "memory"); return x; }
DI uint32_t lds16(uint32_t a) { uint32_t x; asm volatile("ld.shared.u16 %0, [%1];" : "=r"(x) : "r"(a) : "memory"); return x; }
DI uint32_t atoms_add(uint32_t a, uint32_t v) { uint32_t r; asm volatile("atom.shared.add.u32 %0, [%1], %2;" : "=r"(r) : "r"(a), "r"(v) : "memory"); return r; }
DI uint32_t atoms_incp(uint32_t a, bool p) { uint32_t r = 0; asm volatile("{.reg .pred p; setp.ne.b32 p, %2, 0; @p atom.shared.add.u32 %0, [%1], 1;}" : "+r"(r) : "r"(a), "r"((int)p) : "memory"); return r; }
DI uint32_t ldg_poll(const void* a) { uint32_t x; asm volatile("ld.relaxed.gpu.global.u32 %0, [%1];" : "=r"(x) : "l"(a) : "memory"); return x; }
DI uint2 ldg_poll2(const void* a) { uint2 x; asm volatile("ld.relaxed.gpu.global.v2.u32 {%0, %1}, [%2];" : "=r"(x.x), "=r"(x.y) : "l"(a) : "memory"); return x; }
DI void bulk_load(uint32_t dst, const void* src, uint32_t bytes, uint32_t bar) {
  asm volatile("cp.async.bulk.shared::cluster.global.mbarrier::complete_tx::bytes.L2::cache_hint [%0], [%1], %2, [%3], %4;" :: "r"(dst), "l"(src), "r"(bytes), "r"(bar), "l"(pol_first()) : "memory"); }
DI void mbar_expect(uint32_t bar, uint32_t bytes) { asm volatile("mbarrier.arrive.expect_tx.shared::cta.b64 _, [%0], %1;" :: "r"(bar), "r"(bytes) : "memory"); }
DI void mbar_init(uint32_t bar, int n) { asm volatile("mbarrier.init.shared::cta.b64 [%0], %1;" :: "r"(bar), "r"(n) : "memory"); }
DI void tma_load(uint32_t dst, uint64_t tm, int row, uint32_t bar) {
  asm volatile("cp.async.bulk.tensor.2d.shared::cluster.global.mbarrier::complete_tx::bytes.L2::cache_hint [%0], [%1, {%3, %4}], [%2], %5;" :: "r"(dst), "l"(tm), "r"(bar), "r"(0), "r"(row), "l"(pol_first()) : "memory"); }
DI void tma_load_keep(uint32_t dst, uint64_t tm, int row, uint32_t bar) {
  asm volatile("cp.async.bulk.tensor.2d.shared::cluster.global.mbarrier::complete_tx::bytes [%0], [%1, {%3, %4}], [%2];" :: "r"(dst), "l"(tm), "r"(bar), "r"(0), "r"(row) : "memory"); }
DI void tma_store(uint64_t tm, int col, int row, uint32_t src) {
  asm volatile("cp.async.bulk.tensor.2d.global.shared::cta.bulk_group [%0, {%2, %3}], [%1];" :: "l"(tm), "r"(src), "r"(col), "r"(row) : "memory"); }
DI void tma_store_x(uint64_t tm, int col, uint32_t src) {
  if (XPOL & 1) asm volatile("cp.async.bulk.tensor.2d.global.shared::cta.bulk_group.L2::cache_hint [%0, {%2, 0}], [%1], %3;" :: "l"(tm), "r"(src), "r"(col), "l"(pol_first()) : "memory");
  else tma_store(tm, col, 0, src); }
DI void bulk_commit() { asm volatile("cp.async.bulk.commit_group;" ::: "memory"); }
DI void stsm4(uint32_t a, uint32_t x, uint32_t y, uint32_t z, uint32_t w) { asm volatile("stmatrix.sync.aligned.m8n8.x4.shared.b16 [%0], {%1,%2,%3,%4};" :: "r"(a), "r"(x), "r"(y), "r"(z), "r"(w) : "memory"); }
DI void ldsm4(uint32_t* v, uint32_t a) { asm volatile("ldmatrix.sync.aligned.m8n8.x4.shared.b16 {%0,%1,%2,%3}, [%4];" : "=r"(v[0]), "=r"(v[1]), "=r"(v[2]), "=r"(v[3]) : "r"(a) : "memory"); }
DI void ldsm4t(uint32_t& x, uint32_t& y, uint32_t& z, uint32_t& w, uint32_t a) { asm volatile("ldmatrix.sync.aligned.m8n8.x4.trans.shared.b16 {%0,%1,%2,%3}, [%4];" : "=r"(x), "=r"(y), "=r"(z), "=r"(w) : "r"(a) : "memory"); }

__device__ __noinline__ void slow_path(const Params& p) {
  const int lane = threadIdx.x & 31, wid = threadIdx.x >> 5;
  const uint32_t ab = sb + wid * (24 * 528);
  const uint32_t* we = (const uint32_t*)p.we;
  const int nend = min(p.N, (blockIdx.x + 1) * p.NPC);
  auto rowmul = [&](uint32_t hv, const uint32_t* w, float& y0, float& y1) {
#pragma unroll 4
    for (int k = 0; k < 32; k++) {
      const uint32_t hk = __shfl_sync(~0u, hv, k), wa = __ldg(w + 2 * k * 32 + lane), wb = __ldg(w + (2 * k + 1) * 32 + lane);
      y0 = fmaf(bf_lo(hk), bf_lo(wa), fmaf(bf_hi(hk), bf_lo(wb), y0)); y1 = fmaf(bf_lo(hk), bf_hi(wa), fmaf(bf_hi(hk), bf_hi(wb), y1));
    }
  };
  auto act = [](float x) { return x / (1.f + __expf(-x)); };
  auto hrow = [&](int n) { return __ldg(p.h + (size_t)n * 64 + 2 * lane) | ((uint32_t)__ldg(p.h + (size_t)n * 64 + 2 * lane + 1) << 16); };
  const uint32_t wdv = __ldg(we + 128 * 32 + lane), wxv = __ldg((const uint32_t*)p.wx + lane);
  for (int nb = blockIdx.x * p.NPC + wid * 24; nb < nend; nb += 384) {
    const int cnt = min(24, nend - nb);
    for (int n = 0; n < cnt; n++) {
      float y0 = 0.f, y1 = 0.f; rowmul(hrow(nb + n), we, y0, y1);
      sts64(ab + n * 528 + lane * 8, 0, 0); sts64(ab + n * 528 + 256 + lane * 8, __float_as_uint(y0), __float_as_uint(y1));
      if (lane < 4) sts32(ab + n * 528 + 512 + lane * 4, 0);
    }
    __syncwarp();
    for (int base = 0; base < p.E; base += 32) {
      const uint32_t dl = base + lane < p.E ? (uint32_t)(__ldg(p.dst + base + lane) - nb) : 0xFFFFFFFFu;
      uint32_t mk = __ballot_sync(~0u, dl < (uint32_t)cnt);
      while (mk) {
        const int l = __ffs(mk) - 1; mk &= mk - 1;
        const int e = base + l, n = __shfl_sync(~0u, dl, l), s = __ldg(p.src + e);
        const uint32_t a = ab + n * 528;
        float df = 0.f;
        if (lane < 3) df = bf_lo(pack_bf16(bf_lo(__ldg(p.pos + (size_t)(nb + n) * 3 + lane)) - bf_lo(__ldg(p.pos + (size_t)s * 3 + lane)), 0.f));
        float d2 = df * df; d2 += __shfl_xor_sync(~0u, d2, 1); d2 += __shfl_xor_sync(~0u, d2, 2); d2 = __shfl_sync(~0u, d2, 0);
        uint32_t x0, x1; lds64(x0, x1, a + 256 + lane * 8);
        float y0 = fmaf(d2, bf_lo(wdv), __uint_as_float(x0)), y1 = fmaf(d2, bf_hi(wdv), __uint_as_float(x1));
        rowmul(hrow(s), we + 64 * 32, y0, y1);
        for (int k = 0; k < 16; k++) { const float ev = bf_lo(__ldg(p.ea + (size_t)e * 16 + k)); const uint32_t w = __ldg(we + (129 + k) * 32 + lane); y0 = fmaf(ev, bf_lo(w), y0); y1 = fmaf(ev, bf_hi(w), y1); }
        y0 = act(y0); y1 = act(y1);
        float c = y0 * bf_lo(wxv) + y1 * bf_hi(wxv);
#pragma unroll
        for (int o = 16; o; o >>= 1) c += __shfl_xor_sync(~0u, c, o);
        lds64(x0, x1, a + lane * 8);
        sts64(a + lane * 8, __float_as_uint(__uint_as_float(x0) + y0), __float_as_uint(__uint_as_float(x1) + y1));
        if (lane < 3) sts32(a + 512 + lane * 4, __float_as_uint(fmaf(c, df, __uint_as_float(lds32(a + 512 + lane * 4)))));
      }
    }
    __syncwarp();
    for (int n = 0; n < cnt; n++) {
      const uint32_t hv = hrow(nb + n); uint32_t x0, x1; lds64(x0, x1, ab + n * 528 + lane * 8);
      float y0 = 0.f, y1 = 0.f; rowmul(hv, (const uint32_t*)p.wh, y0, y1); rowmul(pack_bf16(__uint_as_float(x0), __uint_as_float(x1)), (const uint32_t*)p.wh + 64 * 32, y0, y1);
      const uint32_t o = badd(hv, pack_bf16(act(y0), act(y1)));
      p.out[(size_t)(nb + n) * 64 + 2 * lane] = (uint16_t)o; p.out[(size_t)(nb + n) * 64 + 2 * lane + 1] = (uint16_t)(o >> 16);
      if (lane < 3) p.out[(size_t)p.N * 64 + (size_t)(nb + n) * 3 + lane] = (uint16_t)pack_bf16(bf_lo(__ldg(p.pos + (size_t)(nb + n) * 3 + lane)) + __uint_as_float(lds32(ab + n * 528 + 512 + lane * 4)), 0.f);
    }
    __syncwarp();
  }
}

__global__ void __launch_bounds__(NT, 1) egnn_kernel(const __grid_constant__ Params p, const __grid_constant__ Maps maps) {
  extern __shared__ __align__(1024) unsigned char smraw[];
  const int tid = threadIdx.x, cta = blockIdx.x;
  const int e0 = cta * p.EPC, nb = max(0, min(p.EPC, p.E - e0)) * 4;
  STAMP(0);
  auto load_idx = [&](int c) {
    const int o = (c & 3) * CH, n = max(0, min(CH, nb - o));
    mbar_expect(BAR_C + c * 8, n);
    if (n) bulk_load(c < 4 ? a_dst(c) : A_SRC + o, (const char*)((c < 4 ? p.dst : p.src) + e0) + o, n, BAR_C + c * 8);
  };
  if (tid == 480 && !p.force_slow) {
#pragma unroll
    for (int c = 0; c < 4; c++) mbar_init(BAR_C + c * 8, 1);
    asm volatile("fence.mbarrier_init.release.cluster;" ::: "memory");
#pragma unroll
    for (int c = 0; c < 4; c++) load_idx(c);
  }
  if ((uint32_t)__cvta_generic_to_shared(smraw) != sb) return;
  if (p.force_slow) { slow_path(p); return; }
  uint32_t ep = ldg_poll(p.s->ep + cta * 32), tgb;
  const uint64_t tmb = (uint64_t)&maps;
  const int lane = tid & 31, wid = __shfl_sync(~0u, tid >> 5, 0), g8 = lane >> 2, q = lane & 3;
  if (wid >= 12) {
    if (tid == 480 || tid == 448) {
#pragma unroll
      for (int c = 0; c < 10; c++) if (tid == 480 || c < 5) mbar_init(BAR_C + (tid == 480 ? 32 : 112) + c * 8, 1);
      asm volatile("fence.mbarrier_init.release.cluster;" ::: "memory");
    }
    if (tid - 416 < 9u) asm volatile("prefetch.tensormap [%0];" :: "l"(tmb + (tid - 416) * 128));
    __syncwarp();
    if (wid == 15) bar_arrive(7, NT); else bar_sync(7, NT);
    if (tid == 480) {
#pragma unroll 1
      for (int c = 4; c < 14; c++) {
        if (c >= WIN) mbar_wait(BAR_C + (c - WIN) * 8, 0);
        if (c < 8) load_idx(c); else { mbar_expect(BAR_C + c * 8, 8192); if (HK) tma_load_keep(A_PT + (c - 8) * 8192, tmb + TM_H, cta * p.NPC + (c - 8) * 64, BAR_C + c * 8); else tma_load(A_PT + (c - 8) * 8192, tmb + TM_H, cta * p.NPC + (c - 8) * 64, BAR_C + c * 8); }
      }
    }
    if (tid == 448) {
      mbar_expect(BAR_W, 2 * 8192 + 2048 + 256);
      tma_load(A_W, tmb + TM_WE, 64, BAR_W); tma_load(A_W + 8192, tmb + TM_WE, 0, BAR_W); tma_load(A_W3, tmb + TM_W3, 129, BAR_W);
      bulk_load(A_WD, p.we + 128 * 64, 128, BAR_W); bulk_load(A_WD + 128, p.wx, 128, BAR_W);
    }
    __syncwarp();
  }

  const int w = wid & 3;
  const uint32_t frag = (w * 16 + (lane & 15)) * 128 + (((lane >> 4) ^ (lane & 7)) << 4), pa = A_POSH + (w * 16 + g8) * 8 + q * 2;
  float a0[32], a1[32];
  float mx = 0.f;
  auto mma = [&](float (&acc)[32], int b, int blk) {
    const uint64_t da = DHI | ((A_PT + blk * 8192) >> 4), db = DHI | ((A_W + b * 8192) >> 4);
    wg_fence();
    ss64<0>(acc, da, db); ss64<1>(acc, da + 2, db + 128); ss64<1>(acc, da + 4, db + 256); ss64<1>(acc, da + 6, db + 384);
    wg_commit();
  };
  auto epi = [&](float (&acc)[32], int b, int blk) {
    uint32_t o[16];
#pragma unroll
    for (int j = 0; j < 16; j++) o[j] = pack_f16(acc[2 * j], acc[2 * j + 1]);
    if (b) {
#pragma unroll
      for (int j = 0; j < 32; j++) mx = fmaxf(mx, fabsf(acc[j]));
    } else {
#pragma unroll
      for (int r = 0; r < 2; r++) {
        const uint32_t T = __byte_perm(lds16(pa + blk * 512 + r * 64), 0, 0x4140);
#pragma unroll
        for (int j = 0; j < 4; j++) o[2 * j + r] &= 0xFFFCFFFCu;
        const uint32_t S = o[r] + o[2 + r] * 4 + o[4 + r] * 16 + o[6 + r] * 64;
        const uint32_t X = (T - S) & 255, Y = X | ((T - ((S + X) & 0xFFFF0000u)) & 0x00FF0000u);
#pragma unroll
        for (int j = 0; j < 4; j++) o[2 * j + r] |= (Y >> (2 * j)) & 0x00030003u;
      }
    }
    const uint32_t a = (b ? A_PT : A_QS) + blk * 8192 + frag;
#pragma unroll
    for (int j = 0; j < 4; j++) stsm4(a ^ (j << 5), o[4 * j], o[4 * j + 1], o[4 * j + 2], o[4 * j + 3]);
  };
  auto p_check = [&](int blk) {
    const uint32_t pm = __reduce_max_sync(~0u, __float_as_uint(mx));
    if (pm > 0x46000000u || (pm < 0x3A800000u && blk * 64 + (w + 1) * 16 <= min(p.NPC, p.N - cta * p.NPC))) sts32(A_MISC, 1);
  };
  if (wid >= 12) {
    const int node0 = cta * p.NPC, nloc = max(0, min(p.NPC, p.N - node0));
    if (w == 3) ep++;
    else {
      const int t = tid - 384;
      uint32_t ps[12], mp = 0;
#pragma unroll
      for (int k = 0; k < 4; k++) {
        ps[3 * k] = ps[3 * k + 1] = ps[3 * k + 2] = 0;
        asm volatile("{.reg .pred p; setp.lt.s32 p, %4, %5;\n @p ld.global.nc.u16 %0, [%3];\n @p ld.global.nc.u16 %1, [%3+2];\n @p ld.global.nc.u16 %2, [%3+4];}"
          : "+r"(ps[3 * k]), "+r"(ps[3 * k + 1]), "+r"(ps[3 * k + 2]) : "l"(p.pos + (size_t)(node0 + t + 96 * k) * 3), "r"(t + 96 * k), "r"(p.N - node0));
      }
      mbar_wait(BAR_W, 0);
#pragma unroll
      for (int k = 0; k < 11; k++) if (k < 10 || w < 2) { uint32_t v[4]; const uint32_t a = A_W + (t + k * 96) * 16; lds128(v, a); sts128(a, bhalf(v[0]), bhalf(v[1]), bhalf(v[2]), bhalf(v[3])); }
      const uint32_t wd = lds32(A_WD + lane * 4), md = amax_warp(wd & 0x7FFF7FFFu);
      bool bad = md - 0x3B00 > 0x680;
      if (w < 2) {
        uint32_t mw = 0;
#pragma unroll
        for (int k = 0; k < 2; k++) { uint32_t v[4]; const uint32_t a = A_W3 + (t + k * 64) * 16; lds128(v, a);
          sts128(a, b2h(bhalf(v[0])), b2h(bhalf(v[1])), b2h(bhalf(v[2])), b2h(bhalf(v[3]))); mw = amax2(amax2(amax2(amax2(mw, v[0]), v[1]), v[2]), v[3]); }
        bad |= amax_warp(mw) - 0x3B00 > 0x680;
      } else {
#pragma unroll
        for (int r = 0; r < 8; r++) sts32(A_WD2 + r * 128 + ((lane * 4) ^ (r << 4)), (r & 1) ? 0 : r == 6 ? 0xF753F753u : b2h(bhalf(wd)));
        const uint32_t x = lds32(A_WD + 128 + lane * 4), ex = min(max(amax_warp(x & 0x7FFF7FFFu) >> 7, 20u), 230u);
        const float sc = __uint_as_float((252 - ex) << 23);
        sts32(A_WD + 128 + lane * 4, pack_f16(bf_lo(x) * sc, bf_hi(x) * sc)); sts32(A_MISC + 12, (ex + 2) << 23);
      }
#pragma unroll
      for (int k = 0; k < 4; k++) {
        const int n = t + 96 * k;
        sts64(A_POSH + n * 8, pack_f16(bf_lo(ps[3 * k]), bf_lo(ps[3 * k + 1])), pack_f16(bf_lo(ps[3 * k + 2]), 1.f));
        sts16(A_POSB + n * 6, ps[3 * k]); sts16(A_POSB + n * 6 + 2, ps[3 * k + 1]); sts16(A_POSB + n * 6 + 4, ps[3 * k + 2]);
        mp = amax2(amax2(mp, ps[3 * k] | (ps[3 * k + 1] << 16)), ps[3 * k + 2]);
      }
      mp = amax_warp(mp);
      if (bad || !(bf_lo(mp) * bf_lo(mp) * bf_lo(md) < 6000.f) || (mp < 0x3B80 && (w + 1) * 32 <= nloc)) sts32(A_MISC, 1);
      proxy_fence();
      if (w == 0) STAMP(16);
      bar_arrive(3, NX + 96);
      ep++;
    }
    bar_sync(6, 128);
    auto store_q = [&](int lo, int hi) {
      if (lane == 0) {
        proxy_fence();
#pragma unroll 1
        for (int b = lo; b < hi && b * 64 < nloc; b++) tma_store(tmb + TM_Q, 0, node0 + b * 64, A_QS + b * 8192);
      }
      __syncwarp();
    };
#pragma unroll 1
    for (int blk = 0; blk < 6; blk += blk ? 1 : 4) {
      mbar_wait(BAR_T + blk * 8, 0);
      if (w == 0 && blk == 5) STAMP(17);
      mma(a0, 0, blk); mma(a1, 1, blk);
      if (w == 3 && blk == QH) { bar_sync(8, NX + 32); store_q(QH0, QH); }
      asm volatile("wgmma.wait_group.sync.aligned 1;" ::: "memory"); fence_regs(a0);
      epi(a0, 0, blk);
      wg_wait0(); fence_regs(a1);
      bar_sync(6, 128);
      if (w == 3 && (blk >= QH || blk < QH0)) store_q(blk, blk + 1);
      if (w == 3) STAMP(18);
      epi(a1, 1, blk);
    }
    p_check(0);
    tgb = ep << 31;
  } else {
    if (tid < (A_CNT - A_MISC) / 16) sts128(A_MISC + tid * 16, 0, tid == 0 ? 16 : 0, 0, 0);
    const uint32_t acnt = A_CNT + ((tid + cta * p.NPC) & 511) * 4;
    sts32(acnt, A_TAB + tid * (CAP * 2));
    if (tid < 32) sts32(A_CNT + 2048 + tid * 4, A_TRASH);
    ep++; tgb = ep << 31;
    const uint32_t tga = (ep & 63) * 0x04000400u, tgh = tga & 0xFFFF0000u;
    {
      const uint32_t x = tga + (512 + (tid & 7) * 4) * 0x10001u;
#pragma unroll
      for (int k = 0; k < 3; k++) if (k < 2 || tid < (G + 1) * 8 - 2 * NX) {
        const uint32_t i = tid + k * NX, hw = ((i >> 3) & 31) - (i & 7) * 4;
        sts128(A_SA + i * 16, x, x + 0x10001u, x + 0x20002u, x + 0x30003u);
        sts32p(A_SA + i * 16 + hw * 4, tgh + (i & 7) * 16 + hw * 4 + 4, hw < 4);
      }
#pragma unroll
      for (int k = 0; k < 6; k++) if (k < 5 || tid < G * 16 - 5 * NX) sts128(A_SB + (tid + k * NX) * 16, tgb, tgb, tgb, tgb);
    }
    bar_sync(7, NT);
    STAMP(23);
    uint32_t d[16], oo[16], xx[16], lc[16], mxx = 0;
#pragma unroll
    for (int c = 0; c < 4; c++) {
      mbar_wait(BAR_C + c * 8, 0);
      if (c == 3) STAMP(1);
      lds128(d + 4 * c, a_dst(c) + tid * 16);
#pragma unroll
      for (int k = 4 * c; k < 4 * c + 4; k++) {
        if (tid * 16 + c * CH >= nb) d[k] = G * p.NPC;
        const uint32_t j = __umulhi(d[k], p.magic);
        xx[k] = atoms_add(A_SA + (j * 128 | ((j * 4) & 0x7C)), 258);
        oo[k] = j * 128;
      }
    }
#pragma unroll
    for (int k = 0; k < 16; k++) { oo[k] |= xx[k] & 0x7E; mxx = max(mxx, xx[k]); }
    if (mxx > tgh + 15900) {
#pragma unroll
      for (int k = 0; k < 16; k++) if (xx[k] > tgh + 15900) oo[k] = G * 128 + 64 + lane * 2;
    }
#pragma unroll
    for (int k = 0; k < 16; k++) sts16(A_SA + oo[k], (d[k] & 511) | tga);
    if (wid == 0) { bar_sync(1, NX); if (lane == 0) { proxy_fence(); tma_store_x(tmb + TM_XA, cta * 192, A_SA); bulk_commit(); } __syncwarp(); } else bar_arrive(1, NX);
    STAMP(2);
    const uint32_t eb = tgb + ((tid * 4 + (cta & 3) * p.EPC) << 16);
#pragma unroll
    for (int c = 0; c < 4; c++) {
      mbar_wait(BAR_C + 32 + c * 8, 0);
      if (wid == 0 && c == 3) STAMP(21);
      lds128(lc + 4 * c, A_SRC + c * CH + tid * 16);
#pragma unroll
      for (int k = 4 * c; k < 4 * c + 4; k++) { lc[k] += eb + ((c * NX * 4 + (k & 3)) << 16); sts32(A_SB + oo[k] * 2, lc[k]); }
    }
    bar_sync(2, NX);
    if (tid == 0) { proxy_fence(); tma_store_x(tmb + TM_XB, cta * 96 + 32, A_SB); bulk_commit(); p.s->ep[cta * 32] = ep; }
    __syncwarp();
    STAMP(3);
    if (mxx > tgh + 15900) {
#pragma unroll
      for (int k = 0; k < 16; k++) {
        const uint32_t j = __umulhi(d[k], p.magic), r = (xx[k] - tgh) / 258 - 62;
        if (r < 31 && j < G)
          asm volatile("st.relaxed.gpu.global.v2.u32 [%0], {%1, %2};" :: "l"(p.s->xe + (j * G + cta) * 32 + r), "r"(lc[k]), "r"((d[k] & 511) | (ep << 9)) : "memory");
      }
    }
    __syncwarp();
    constexpr int JS = 12; const int j0 = wid;
#pragma unroll
    for (int k = 0; k < 7; k++) if (k < 6 || tid < 385 * CAP / 8 + 9 - 6 * NX) sts128(A_TAB + (tid + k * NX) * 16, 0, 0, 0, 0);
    bar_sync(3, NX + 96);
    STAMP(12);
    const char* xin = (const char*)(p.s->x + cta * G * 24);
    uint32_t pk[11];
    const uint32_t rot = (lane + cta) & 31;
    auto poll_a = [&]() {
#pragma unroll
      for (int k = 0; k < 11; k++) pk[k] = ldg_poll(xin + (j0 + JS * k) * FS + rot * 4);
    };
    uint32_t xs = ~0u; uint2 xv;
    const uint32_t t0 = (wid >> 2) * BS + 128 + w * 256 + rot * 8, tx = lane ? tga : tgh;
    const uint32_t h1 = (cta & 31) * 4 + 4 + 62 * 258;
    int spin = 0;
    auto copy_b = [&]() {
      const uint32_t o = (j0 + JS * (lane >> 4)) * FS + 128 + (lane & 15) * 16, a = A_IN + ((wid >> 2) + 3 * (lane >> 4)) * BS + 128 + w * 256 + (lane & 15) * 16;
#pragma unroll
      for (int k = 0; k < 6; k++) if (k < 5 || lane < 16)
        asm volatile("cp.async.cg.shared.global.L2::cache_hint [%0], [%1], 16, %2;" :: "r"(a + k * 6 * BS), "l"(xin + o + k * 2 * JS * FS), "l"(pol_first()) : "memory");
    };
    {
      const int blk = (wid >> 2) + 1;
      mbar_wait(BAR_T + blk * 8, 0);
      if (wid == 8) STAMP(22);
      mma(a0, 0, blk); mma(a1, 1, blk);
      asm volatile("wgmma.wait_group.sync.aligned 1;" ::: "memory"); fence_regs(a0);
      epi(a0, 0, blk);
      bar_arrive(8, NX + 32);
      if (PG < 0) poll_a();
      wg_wait0(); fence_regs(a1);
      bar_sync(13 + (wid >> 2), 128);
      epi(a1, 1, blk);
      p_check(blk);
      if (PG >= 0) { mbar_wait(BAR_T + PG * 8, 0); poll_a(); }
      if (wid == 8) STAMP(24);
    }
    {
      {
        for (;;) {
          uint32_t mh = 0, bad = 0;
#pragma unroll
          for (int k = 0; k < 11; k++) { pk[k] ^= tx; mh = max(mh, pk[k]); bad |= pk[k]; }
          if (!__any_sync(~0u, bad & (lane ? 0xFC00FC00u : 0xFC000000u))) {
            if (__shfl_sync(~0u, mh, 0) > h1) {
              uint32_t base = 0;
#pragma unroll
              for (int k = 0; k < 11; k++) {
                const uint32_t c = (max(__shfl_sync(~0u, pk[k], 0), h1) - h1) / 258;
                if (lane - base < c) xs = (j0 + JS * k) * 32 + lane - base;
                base += c;
              }
              if (base > 31) { sts32(A_MISC, 1); xs = ~0u; }
              if (xs != ~0u) xv = ldg_poll2(p.s->xe + cta * G * 32 + xs);
              __syncwarp();
            }
            break;
          }
          if (++spin > 2000000) __trap();
          poll_a();
        }
        STAMP(14); if (wid == 8) STAMP(25);
        uint32_t r0[11], r1[11];
#pragma unroll
        for (int k = 0; k < 11; k++) {
          if (lane == 0) pk[k] = (512 + rot) * 0x10001u;
          r0[k] = atoms_add(A_CNT + (pk[k] & 0xFFFF) * 4, 2);
          r1[k] = atoms_add(A_CNT + (pk[k] >> 16) * 4, 2);
        }
#pragma unroll
        for (int k = 0; k < 11; k++) { sts16(min(r0[k], A_IN - 2), t0 + 3 * k * BS); sts16(min(r1[k], A_IN - 2), t0 + 3 * k * BS + 4); }
        if (wid == 8) STAMP(26);
      }
    }
    if (tid == 0) { asm volatile("cp.async.bulk.wait_group.read 0;" ::: "memory"); if (CBH) mbar_wait(BAR_T + 40, 0); mbar_arrive(BAR_X); }
    __syncwarp();
    mbar_wait(BAR_X, 0);
    copy_b();
    STAMP(4);
    if (xs != ~0u) {
      for (int i = 0; (((xv.x ^ tgb) >> 31) | ((xv.y >> 9) ^ (ep & 0x7FFFFF))) && i < 2000000; i++) xv = ldg_poll2(p.s->xe + cta * G * 32 + xs);
      const uint32_t n = atoms_add(A_XC + (xs >> 7) * 4, 4), t = (xs >> 7) * BS + 4 + min(n, 120u);
      if (n > 120) sts32(A_MISC, 1);
      sts16(min(atoms_add(A_CNT + (xv.y & 511) * 4, 2), A_IN - 2), t);
      sts32(A_IN + t, xv.x);
    }
    __syncwarp();
    bar_sync(4, NX);
    STAMP(5);
    {
      const uint32_t dg = (lds32(acnt) - (A_TAB + tid * (CAP * 2))) >> 1;
      const uint32_t dr = atoms_add(A_DH + min(dg, 63u) * 4, 1);
      bar_sync(5, NX);
      uint32_t hb, ha; lds64(hb, ha, A_DH + (62 - 2 * lane) * 4);
      uint32_t inc = ha + hb;
#pragma unroll
      for (int o = 1; o < 32; o <<= 1) { const uint32_t y = __shfl_up_sync(~0u, inc, o); if (lane >= o) inc += y; }
      const uint32_t idx = 63 - min(dg, 63u);
      const uint32_t e2 = __shfl_sync(~0u, (inc - hb) | ((inc - hb - ha) << 16), idx >> 1);
      const uint32_t pos = ((idx & 1) ? (e2 & 0xFFFF) : (e2 >> 16)) + dr;
      sts16(A_ROWS + pos * 2, tid);
      if (!(pos & 7)) sts32(A_LEN + (pos >> 1), max(1u, (dg + 1) >> 1));
      if (dg > CAP) sts32(A_MISC, 1);
    }
    STAMP(6);
    if (tid == 0) sts32(A_IN, 0xFFFF);
    for (;;) {
      asm volatile("cp.async.wait_all;" ::: "memory");
      __syncwarp();
      uint32_t bad = 0;
#pragma unroll
      for (int k = 0; k < 11; k++) { uint32_t x, y; lds64(x, y, A_IN + t0 + 3 * k * BS); bad |= (x ^ tgb) | (y ^ tgb); }
      if (!__any_sync(~0u, bad >> 31) || ++spin > 2000000) break;
      copy_b();
    }
    STAMP(7);
  }
  if (wid == 15) {
    bar_arrive(11, NT);
    if (lane == 0) { bulk_commit(); asm volatile("cp.async.bulk.wait_group 0;" ::: "memory"); }
    __syncwarp();
    if (lane < NREP) asm volatile("red.relaxed.gpu.global.add.u32 [%0], 1;" :: "l"(p.s->cnt + lane * 32) : "memory");
    if (lane == 0) {
      STAMP(19);
      const uint32_t nbe = (p.E / G) & ~15u;
#pragma unroll 1
      for (int i = 0; i < PFA; i++)
        if (nbe) asm volatile("cp.async.bulk.prefetch.L2.global [%0], %1;" :: "l"((const char*)p.ea + (size_t)(i * G + cta) * nbe), "r"(nbe) : "memory");
      uint32_t c; int spin = 0;
      do { asm volatile("ld.acquire.gpu.global.u32 %0, [%1];" : "=r"(c) : "l"(p.s->cnt + (cta % NREP) * 32) : "memory"); } while ((int)(c - ep * G) < 0 && ++spin < 20000000);
      mbar_arrive(BAR_Q);
      STAMP(20);
    }
    __syncwarp();
  }
  uint32_t W3[16], PB[16], WX[8];
#pragma unroll
  for (int k = 0; k < 4; k++) ldsm4t(W3[4 * k], W3[4 * k + 1], W3[4 * k + 2], W3[4 * k + 3], A_W3 + (lane & 15) * 128 + ((((lane >> 4) + 2 * k) ^ (lane & 7)) << 4));
#pragma unroll
  for (int j = 0; j < 8; j++) WX[j] = lds32(A_WD + 128 + j * 16 + q * 4);
  uint32_t A2[4];
  const uint32_t ring = 4096 + wid * 4096, ering = (wid < 8 ? 69632 : A_E3 - 8 * 1536) + wid * 1536;
  const int oc = lane >> 3;
  const int r7 = lane & 7, ro = r7 >> 1, ri = 2 * (oc & 1) + (r7 & 1);
  uint64_t qp0 = (uint64_t)p.s->q + ((r7 ^ (2 * oc)) << 4), qp1 = qp0 ^ 16, epp = (uint64_t)p.ea + (((lane ^ oc) & 1) << 4) - (tgb >> 11);
  uint32_t dq = ring + oc * 512 + r7 * 16, de = ering + ((lane * 16) ^ ((oc >> 1) * 64));
  uint32_t rq = ring + (4 * ro + ri) * 128 + (((oc >> 1) ^ r7) << 4), re = ering + ro * 128 + ((ri ^ (2 * (ro >> 1))) << 5) + ((((oc >> 1) ^ ro) & 1) << 4);
  A2[0] = (g8 >> 1) == q ? ((g8 & 1) ? 0x3C000000u : 0x3C00u) : 0;
  A2[0] += lds32(A_MISC + 8); A2[1] = A2[0] + lds32(A_MISC + 8);
  asm volatile("" : "+l"(qp0), "+l"(qp1), "+l"(epp), "+r"(dq), "+r"(de), "+r"(rq), "+r"(re));
  if (wid < 15) { bar_sync(11, NT); if (wid == 14) bar_arrive(12, 64); } else bar_sync(12, 64);
  STAMP(13);
  if (lds32(A_MISC)) { sts32(A_MISC + 12, dq ^ de ^ rq ^ re ^ (uint32_t)qp0 ^ (uint32_t)qp1 ^ (uint32_t)(epp ^ (epp >> 32)) ^ A2[1]); __syncthreads(); slow_path(p); return; }

  uint32_t MS[8], acc[16], m[16], yh[8], A1[4], OP, TA, D = 0, U = 0, tt, tn, rec, rn, sl;
  re += lds32(A_MISC) + 1024 - ering; de += lds32(A_MISC) + 1024 - re; const uint32_t rtop = re + lds32(A_MISC);
  uint64_t pol; asm("createpolicy.fractional.L2::evict_first.b64 %0, " EFR ";" : "=l"(pol));
  if (EKEEP) asm("createpolicy.range.global.L2::" EPOL ".L2::evict_first.b64 %0, [%1], %2, %3;" : "=l"(pol) : "l"(p.ea), "r"(p.E * EKEEP), "r"(p.E * 32));
  const uint32_t zr = p.force_slow;
  uint64_t y64[4] = {0, 0, 0, 0};
  uint32_t rk[4];
#pragma unroll
  for (int k = 0; k < 4; k++) rk[k] = (rq ^ (k * 32)) + (RK ? lds32(A_MISC) : 0);
  uint32_t nd3, mk, ln, gl = 10, gc = 0;
  auto lane_id = []() { uint32_t l; asm volatile("mov.u32 %0, %%laneid;" : "=r"(l)); return l; };
  auto slot_node = [&](uint32_t l) { return __shfl_sync(~0u, nd3, ((l >> 2) & 6) | ((l >> 1) & 1)); };
  auto lswitch = [&]() {
    const uint32_t l = lane_id();
    TA = A_TAB + (ln ? (slot_node(l) >> gl) & 1023 : 384) * (CAP * 2) + ((l >> 1) & 2);
    if (ln) mk |= 32u << (ln & 255);
    else if (atoms_incp(A_MISC + 4, l == 0) == 31) {
      proxy_fence();
      mbar_expect(BAR_U, 16384);
      tma_load(A_TAB, tmb + TM_WH, 0, BAR_U); tma_load(A_TAB + 8192, tmb + TM_WH, 64, BAR_U);
    }
    __syncwarp();
    ln >>= 8; gl += 10;
  };
  auto pswitch = [&]() {
    const uint32_t l = lane_id(), nd = (nd3 >> gc) & 1023;
    const uint32_t a = ((l & 8) ? A_WD2 + (l & 7) * 144 : A_PT + nd * 128 + ((nd & 7) << 4)) ^ (l & 16);
#pragma unroll
    for (int k = 0; k < 4; k++) ldsm4t(PB[4 * k], PB[4 * k + 1], PB[4 * k + 2], PB[4 * k + 3], a ^ (k << 5));
    OP = lds16(A_POSH + __shfl_sync(~0u, nd, l >> 2) * 8 + (l & 3) * 2) * 0x10001;
  };
  auto flush = [&](int hf, uint32_t g) {
    const uint32_t l = lane_id(), nd = (nd3 >> g) & 1023, a = A_PT + nd * 128 + (((l >> 3) ^ (nd & 7)) << 4);
    stsm4(a ^ (hf << 6), MS[4 * hf], MS[4 * hf + 1], MS[4 * hf + 2], MS[4 * hf + 3]);
    if (hf) { sts16(A_POSH + __shfl_sync(~0u, nd, l >> 2) * 8 + (l & 3) * 2, hadd(U, U >> 16)); U = 0; }
#pragma unroll
    for (int j = 4 * hf; j < 4 * hf + 4; j++) MS[j] = 0;
  };
  auto look1 = [&]() { asm volatile("ld.volatile.shared.u16 %0, [%1];" : "=r"(tn) : "r"(TA) : "memory"); TA += 4; };
  auto look2 = [&]() {
    asm volatile("ld.volatile.shared.u32 %0, [%1];" : "=r"(rn) : "r"(A_IN + tn) : "memory");
    tt = __umulhi(tn, 3728271u) * p.EPC4 + (rn >> 16); rn &= 0xFFFF;
    if (ABL & 1) tt = (tt & 0x1FFFF) + 65536;
  };
  auto issue_q = [&](uint32_t rec) {
#pragma unroll
    for (int i = 0; i < 4; i++)
      if (ABL & 2) asm volatile("{.reg .b64 a; .reg .pred p, l; setp.eq.u32 p, %2, 0xFFFF; setp.ge.u32 l, %3, 8; mad.wide.u32 a, %2, 128, %1;\n @l cp.async.cg.shared.global [%0], [a], 16, p;}"
        :: "r"(dq + i * 128), "l"((i & 1) ? qp1 : qp0), "r"(__shfl_sync(~0u, rec, 2 * i, 8)), "r"(zr) : "memory");
      else asm volatile("{.reg .b64 a; .reg .pred p; setp.eq.u32 p, %2, 0xFFFF; mad.wide.u32 a, %2, 128, %1;\n cp.async.cg.shared.global [%0], [a], 16, p;}"
        :: "r"(dq + i * 128), "l"((i & 1) ? qp1 : qp0), "r"(__shfl_sync(~0u, rec, 2 * i, 8)) : "memory");
    asm volatile("cp.async.commit_group;" ::: "memory");
    dq ^= 2048;
  };
  auto issue_e = [&](uint32_t a) {
    if (ABL & 2) asm volatile("{.reg .b64 a; .reg .pred p, l; setp.eq.u32 p, %3, 0xFFFF; setp.ge.u32 l, %5, 8; mad.wide.u32 a, %2, 32, %1;\n @l cp.async.cg.shared.global.L2::cache_hint [%0], [a], 16, p, %4;}"
      :: "r"(a), "l"(epp), "r"(tt), "r"(rn), "l"(pol), "r"(zr) : "memory");
    else asm volatile("{.reg .b64 a; .reg .pred p; setp.eq.u32 p, %3, 0xFFFF; mad.wide.u32 a, %2, 32, %1;\n cp.async.cg.shared.global.L2::cache_hint [%0], [a], 16, p, %4;}"
      :: "r"(a), "l"(epp), "r"(tt), "r"(rn), "l"(pol) : "memory");
  };
  auto act = [&](const uint32_t* y, int k) {
#pragma unroll
    for (int i = 0; i < 4; i++) { m[4 * k + i] = hsilu(y[i]); MS[2 * k + (i >> 1)] = hadd(MS[2 * k + (i >> 1)], m[4 * k + i]); }
  };
  auto cfin = [&](uint32_t d) {
    uint32_t c0_ = 0, c1_ = 0;
#pragma unroll
    for (int k = 0; k < 4; k++) { const int kk = (VAR & 32) ? k : k ^ 2; hmma(c0_, c1_, m + 4 * kk, WX[2 * kk], WX[2 * kk + 1]); }
    U = hfma(__byte_perm(c0_, c1_, 0x5410), d, U);
  };
  auto events = [&]() {
    if (mk & 1) flush(1, gc - 10);
    if (mk & 2) { flush(0, gc); gc += 10; pswitch(); }
    if (mk & 32) lswitch();
    if (mk < 16) {
      const uint32_t l = lane_id(); int cta; asm volatile("mov.u32 %0, %%ctaid.x;" : "=r"(cta));
      rec = ((slot_node(l) >> (mk < 8 ? 20 : (l & 4) ? 10 : 0)) & 1023) + cta * p.NPC;
      if (rec >= p.N || (mk < 8 && (l & 4))) rec = 0xFFFF;
      qp0 = (uint64_t)p.h + (qp0 & 127); qp1 = qp0 ^ 16;
    }
  };
  auto step = [&](uint32_t st) {
    asm volatile("cp.async.wait_group 1;" ::: "memory");
    __syncwarp();
    if (YP == 2) {
#pragma unroll
      for (int j = 4; j < 8; j++) hmma(yh[2 * j - 8], yh[2 * j - 7], A1, W3[2 * j], W3[2 * j + 1]);
    }
    uint32_t E[4];
    ldsm4(E, re + ering);
#pragma unroll
    for (int k = 0; k < 4; k++) ldsm4(acc + 4 * k, rk[k] + st);
    look2();
    issue_q(rec);
    issue_e(re + de); rec = rn;
    look1();
    re = __viaddmin_u32(re, -512, rtop);
    if (ABL & 4) { U ^= (E[0] ^ acc[0] ^ acc[4] ^ acc[8] ^ acc[12]) & zr; return; }
#pragma unroll
    for (int i = 0; i < 4; i++) A1[i] = pack_f16(__uint_as_float(__byte_perm(E[i], 0, 0x1044)), bf_hi(E[i]));
    const uint32_t Sa = acc[0] + acc[2] * 4 + acc[4] * 16 + acc[6] * 64, Sb = acc[1] + acc[3] * 4 + acc[5] * 16 + acc[7] * 64;
    const uint32_t Dp = D;
    D = hsub(OP, __byte_perm(Sa, Sb, 0x6420));
    const __half2 d = *(const __half2*)&D, x = __hmul2(d, d), y = __hmul2(__high2half2(d), __high2half2(d));
    A2[2] = *(const uint32_t*)&x; A2[3] = *(const uint32_t*)&y;
    if (YP == 1) {
#pragma unroll
      for (int i = 0; i < 4; i++) asm volatile("mov.b64 {%0, %1}, %2;" : "=r"(yh[2 * i]), "=r"(yh[2 * i + 1]) : "l"(y64[i]));
    }
    if (VAR & 1) yh[4] |= A1[3] & zr;
    if (VAR & 2) yh[6] |= A2[3] & zr;
    act(yh, 2); act(yh + 4, 3);
#pragma unroll
    for (int j = 0; j < 8; j++) { if (YP != 2 || j < 4) hmma(acc[2 * j], acc[2 * j + 1], A1, W3[2 * j], W3[2 * j + 1]); hmma(acc[2 * j], acc[2 * j + 1], A2, PB[2 * j], PB[2 * j + 1]); }
    if (VAR & 4) m[(VAR & 32) ? 0 : 8] |= acc[0] & zr;
    cfin(Dp);
    if (VAR & 8) acc[6] |= acc[14] & zr;
    if (VAR & 16) acc[7] |= acc[10] & zr;
    if (VAR & 64) acc[5] |= acc[8] & zr;
    if (VAR & 128) acc[3] |= tt & zr;
    if (VAR & 256) acc[6] |= U & zr;
    if (LK) acc[LK] |= tn & zr;
    act(acc, 0); act(acc + 4, 1);
#pragma unroll
    for (int i = 0; i < 8; i++) yh[i] = acc[8 + i];
    if (YP == 1) {
#pragma unroll
      for (int i = 0; i < 4; i++) asm volatile("mov.b64 %0, {%1, %2};" : "=l"(y64[i]) : "r"(yh[2 * i]), "r"(yh[2 * i + 1]));
    }
  };
#pragma unroll
  for (int i = 0; i < 8; i++) { m[i] = 0; yh[i] = 0; MS[i] = 0; A1[i & 3] = 0; }
  { const uint32_t sc = p.sched[wid], g0 = sc & 63, g1 = (sc >> 6) & 63, g2 = sc >> 12;
    TA = A_TAB + lds16(A_ROWS + g0 * 16 + oc * 4 + (lane & 2)) * (CAP * 2) + ((lane >> 1) & 2);
    nd3 = lds16(A_ROWS + g0 * 16 + r7 * 2) | (lds16(A_ROWS + g1 * 16 + r7 * 2) << 10) | (lds16(A_ROWS + g2 * 16 + r7 * 2) << 20);
    ln = __reduce_max_sync(~0u, lds32(A_LEN + g0 * 4) | (lds32(A_LEN + g1 * 4) << 8) | (lds32(A_LEN + g2 * 4) << 16));
    mk = 16u << (ln & 255); ln >>= 8;
    look1();
    uint32_t ra = 0, rb = 0, ea = re + de; rn = 0;
#pragma unroll 1
    for (int k = 0; k < 3; k++) { if (mk & 32) lswitch(); ra = rb; rb = rn; look2(); if (k < 2) issue_e(ea); ea -= 512; look1(); mk >>= 1; }
    mbar_wait(BAR_Q, 0);
    STAMP(8);
    issue_q(ra);
    pswitch();
    issue_q(rb); issue_e(re + de - 1024); rec = rn;
  }
  sl = 2048;
  {
#pragma unroll 1
    do {
      if ((mk & 35) || mk < 16) events();
      sl ^= 2048; step(sl); mk >>= 1;
    } while (mk >= 4);
  }
  sl += lds32(A_MISC); rq = rk[0] + lds32(A_MISC); dq = (dq + lds32(A_MISC)) & ~2048u;
  if (mk & 1) flush(1, gc - 10);
  if (YP == 2) {
#pragma unroll
    for (int j = 4; j < 8; j++) hmma(yh[2 * j - 8], yh[2 * j - 7], A1, W3[2 * j], W3[2 * j + 1]);
  }
  act(yh, 2); act(yh + 4, 3); cfin(D);
  flush(0, gc); flush(1, gc);
  STAMP(9);
  {
    int cta; asm volatile("mov.u32 %0, %%ctaid.x;" : "=r"(cta));
    const uint32_t l = lane_id(), node0 = cta * p.NPC; const int nloc = min(p.NPC, p.N - (int)node0);
    constexpr uint64_t dW = DHI | (A_TAB >> 4);
    float y1[32], y2[32];
    uint32_t H[16], po[3];
    auto rows = [&](uint32_t* v, uint32_t nd, int stride) {
      const uint32_t a = A_PT + nd * 128 + (((l >> 4) ^ (nd & 7)) << 4);
#pragma unroll
      for (int k = 0; k < 4; k++) ldsm4(v + 4 * k, a ^ (k << 5));
#pragma unroll
      for (int j = 0; j < 16; j += stride) v[j] = h2b(v[j]);
    };
    asm volatile("cp.async.wait_group 1;" ::: "memory");
    __syncwarp();
    rows(m, (nd3 >> ((l & 8) ? 10 : 0)) & 1023, 1);
#pragma unroll
    for (int k = 0; k < 4; k++) ldsm4(H + 4 * k, (rq ^ (k * 32)) + (sl ^ 2048));
    mbar_wait(BAR_U, 0);
    STAMP(10);
    wg_fence();
    rs64<0>(y1, m, dW + 512); rs64<1>(y1, m + 4, dW + 640); rs64<1>(y1, m + 8, dW + 768); rs64<1>(y1, m + 12, dW + 896);
    rs64<1>(y1, H, dW); rs64<1>(y1, H + 4, dW + 128); rs64<1>(y1, H + 8, dW + 256); rs64<1>(y1, H + 12, dW + 384);
    wg_commit();
    { const uint32_t n0 = __shfl_sync(~0u, nd3, (l >> 2) & 6), n1 = __shfl_sync(~0u, nd3, ((l >> 2) & 6) | 1);
#pragma unroll
      for (int g = 0; g < 3; g++) po[g] = ((n0 >> (10 * g)) & 1023) | (((n1 >> (10 * g)) & 1023) << 16); }
    const uint64_t ob = (uint64_t)(p.out + (size_t)node0 * 64) + (((l & 7) ^ ((l >> 2) & 6)) << 4);
    wg_wait0(); fence_regs(y1);
    rows(m, nd3 >> 20, 2);
    const float ov = y1[0] * y1[2];
    auto fin = [&](uint32_t x, float a, float b) { return badd(x, pack_bf16(silu(a), silu(b))); };
    auto put = [&](uint32_t a, uint32_t nn) {
      uint32_t v[8]; lds128(v, a); lds128(v + 4, a + 128);
#pragma unroll
      for (int i = 0; i < 2; i++)
        asm volatile("{.reg .pred p; .reg .b64 a; setp.lt.s32 p, %0, %1; mad.wide.u32 a, %0, 128, %2; @p st.global.v4.u32 [a], {%3,%4,%5,%6};}"
          :: "r"(i ? nn >> 16 : nn & 0xFFFF), "r"(nloc), "l"(ob ^ (i << 4)), "r"(v[4 * i]), "r"(v[4 * i + 1]), "r"(v[4 * i + 2]), "r"(v[4 * i + 3]) : "memory");
    };
#pragma unroll
    for (int j = 0; j < 4; j++) H[j] = fin(H[j], y1[2 * j], y1[2 * j + 1]);
    wg_fence();
    rs64<0>(y2, m, dW + 512); rs64<1>(y2, m + 4, dW + 640); rs64<1>(y2, m + 8, dW + 768); rs64<1>(y2, m + 12, dW + 896);
    wg_commit();
#pragma unroll
    for (int j = 4; j < 10; j++) H[j] = fin(H[j], y1[2 * j], y1[2 * j + 1]);
    asm volatile("cp.async.wait_group 0;" ::: "memory");
    __syncwarp();
    wg_wait0(); fence_regs(y2);
#pragma unroll
    for (int k = 0; k < 4; k++) ldsm4(m + 4 * k, (rq ^ (k * 32)) + sl);
#pragma unroll
    for (int j = 10; j < 13; j++) H[j] = fin(H[j], y1[2 * j], y1[2 * j + 1]);
    wg_fence();
    rs64<1>(y2, m, dW); rs64<1>(y2, m + 4, dW + 128); rs64<1>(y2, m + 8, dW + 256); rs64<1>(y2, m + 12, dW + 384);
    wg_commit();
#pragma unroll
    for (int j = 13; j < 16; j++) H[j] = fin(H[j], y1[2 * j], y1[2 * j + 1]);
#pragma unroll
    for (int k = 0; k < 4; k++) stsm4((rq ^ (k * 32)) + (sl ^ 2048), H[4 * k], H[4 * k + 1], H[4 * k + 2], H[4 * k + 3]);
    __syncwarp();
    put(dq + (sl ^ 2048), po[0]); put(dq + 256 + (sl ^ 2048), po[1]);
    wg_wait0(); fence_regs(y2);
    sts32p(A_MISC + 8, 1, !(fabsf(ov * y2[0] * 0.f) < 1.f));
#pragma unroll
    for (int j = 0; j < 16; j += 2) m[j] = fin(m[j], y2[2 * j], y2[2 * j + 1]);
#pragma unroll
    for (int k = 0; k < 4; k++) stsm4((rq ^ (k * 32)) + sl, m[4 * k], m[4 * k + 1], m[4 * k + 2], m[4 * k + 3]);
    __syncwarp();
    put(dq + sl, po[2]);
    __syncthreads();
    uint32_t x[3]; bool bad = lds32(A_MISC + 8);
#pragma unroll
    for (int k = 0; k < 3; k++) {
      const uint32_t i = min(threadIdx.x + k * NT, 1151u), u = lds16(A_POSH + i * 2 + i / 3 * 2);
      bad |= (u & 0x7C00) == 0x7C00;
      x[k] = pack_bf16(fmaf(__half2float(__ushort_as_half(u)), __uint_as_float(lds32(A_MISC + 12)), bf_lo(lds16(A_POSB + i * 2))), 0.f);
    }
    uint16_t* op = p.out + (size_t)p.N * 64 + (size_t)node0 * 3 + threadIdx.x;
#pragma unroll
    for (int k = 0; k < 3; k++)
      asm volatile("{.reg .pred p; setp.lt.s32 p, %0, %1; @p st.global.u16 [%2], %3;}" :: "r"(threadIdx.x + k * NT), "r"(nloc * 3), "l"(op + k * NT), "h"((uint16_t)x[k]) : "memory");
    if (__syncthreads_or(bad) && !ABL) { slow_path(p); return; }
  }
  STAMP(11);
}

}

typedef CUresult (*EncodeFn)(CUtensorMap*, CUtensorMapDataType, cuuint32_t, void*, const cuuint64_t*, const cuuint64_t*, const cuuint32_t*, const cuuint32_t*,
                             CUtensorMapInterleave, CUtensorMapSwizzle, CUtensorMapL2promotion, CUtensorMapFloatOOBfill);

extern "C" void kernel_launch(void* const* d_in, const int* in_sizes, int n_in, void* d_out, int out_size) {
  Params p; Maps maps;
  p.h = (const uint16_t*)d_in[0]; p.pos = (const uint16_t*)d_in[1]; p.ea = (const uint16_t*)d_in[2];
  p.src = (const int*)d_in[3]; p.dst = (const int*)d_in[4];
  p.we = (const uint16_t*)d_in[5]; p.wx = (const uint16_t*)d_in[6]; p.wh = (const uint16_t*)d_in[7];
  p.out = (uint16_t*)d_out;
  p.N = in_sizes[0] / 64; p.E = in_sizes[3];
  p.NPC = (p.N + G - 1) / G;
  p.EPC = ((p.E + G * 4 - 1) / (G * 4)) * 4;
  p.magic = (uint32_t)((1ull << 32) / (uint64_t)p.NPC) + 1;
  const uint32_t sched[16] = {0x2d504, 0x29783, 0x2b8c2, 0x2a38b, 0x28448, 0x1f68c, 0x185d3, 0x22747, 0x2558a, 0x2e345, 0x2f9c0, 0x2c901, 0x26646, 0x216c9, 0x1c550, 0x2048f};
  for (int i = 0; i < 16; i++) p.sched[i] = sched[i];
  p.EPC4 = p.EPC * 4;
  uint64_t al = (uint64_t)d_out;
  for (int i = 0; i < 8; i++) if (i != 1) al |= (uint64_t)d_in[i];
  p.force_slow = (al & 127) || (p.E & 3) || p.NPC > 384 || p.NPC < 2 || p.EPC > 6144;
  cudaGetSymbolAddress((void**)&p.s, g_s);
  void* fn = nullptr; cudaDriverEntryPointQueryResult qr;
  cudaGetDriverEntryPoint("cuTensorMapEncodeTiled", &fn, cudaEnableDefault, &qr);
  auto mk = [&](CUtensorMap* tm, void* base, int rows, int box) {
    const cuuint64_t dim[2] = {64, (cuuint64_t)rows}, str[1] = {128}; const cuuint32_t bx[2] = {64, (cuuint32_t)box}, es[2] = {1, 1};
    ((EncodeFn)fn)(tm, CU_TENSOR_MAP_DATA_TYPE_BFLOAT16, 2, base, dim, str, bx, es, CU_TENSOR_MAP_INTERLEAVE_NONE, CU_TENSOR_MAP_SWIZZLE_128B,
                   CU_TENSOR_MAP_L2_PROMOTION_NONE, CU_TENSOR_MAP_FLOAT_OOB_FILL_NONE);
  };
  mk(&maps.m[TM_H / 128], d_in[0], p.N, 64); mk(&maps.m[TM_WE / 128], d_in[5], 145, 64); mk(&maps.m[TM_WH / 128], d_in[7], 128, 64);
  mk(&maps.m[TM_Q / 128], p.s->q, p.N, 64); mk(&maps.m[TM_O / 128], d_out, p.N, 64); mk(&maps.m[TM_O2 / 128], d_out, p.N, (p.NPC & 63) ? (p.NPC & 63) : 64);
  mk(&maps.m[TM_W3 / 128], d_in[5], 145, 16);
  for (int k = 0; k < 2; k++) {
    const cuuint64_t dim[2] = {(cuuint64_t)G * (192 >> k), (cuuint64_t)G}, str[1] = {(cuuint64_t)G * FS}; const cuuint32_t bx[2] = {64, G}, es[2] = {1, 1};
    ((EncodeFn)fn)(&maps.m[TM_XA / 128 + k], k ? CU_TENSOR_MAP_DATA_TYPE_UINT32 : CU_TENSOR_MAP_DATA_TYPE_UINT16, 2, p.s->x, dim, str, bx, es, CU_TENSOR_MAP_INTERLEAVE_NONE,
                   CU_TENSOR_MAP_SWIZZLE_NONE, CU_TENSOR_MAP_L2_PROMOTION_NONE, CU_TENSOR_MAP_FLOAT_OOB_FILL_NONE);
  }
  cudaFuncSetAttribute(egnn_kernel, cudaFuncAttributeMaxDynamicSharedMemorySize, SMEM);
  egnn_kernel<<<G, NT, SMEM>>>(p, maps);
}
```

```cpp
#include <cuda_runtime.h>
#include <cuda_bf16.h>
#include <cuda_fp16.h>
#include <cuda.h>
#include <stdint.h>

#define SCH 2
#define PFA 6
#define PL 0
#define T3 0
#define FR 2
#define XD 0
#define WIN 6
namespace {

constexpr int G = 132;
constexpr int NT = 512;
constexpr int CAP = 48;
constexpr int FS = 384;
constexpr int BS = 1152;
constexpr uint32_t sb = 1024;

constexpr uint32_t A_RING = sb;
constexpr uint32_t A_PT = A_RING + 16 * 5120;
constexpr uint32_t A_W3 = A_PT + 49152;
constexpr uint32_t A_TAB = A_W3 + 2048;
constexpr uint32_t A_IN = A_TAB + 37888;
constexpr uint32_t A_WD = A_IN + G * FS + 512;
constexpr uint32_t A_WD2 = A_WD + 256;
constexpr uint32_t A_BAR = A_WD2 + 1024;
constexpr uint32_t A_MISC = A_BAR + 160;
constexpr uint32_t A_DH = A_MISC + 16;
constexpr uint32_t A_CNT = A_DH + 256;
constexpr uint32_t A_POSH = A_CNT + 2176;
constexpr uint32_t A_POSB = A_POSH + 3072;
constexpr uint32_t A_ROWS = A_POSB + 2304;
constexpr uint32_t A_LEN = A_ROWS + 768;
constexpr uint32_t A_END = A_LEN + 192;
constexpr uint32_t A_XC = A_TAB + 385 * CAP * 2, A_TRASH = A_XC + 144;
constexpr uint32_t A_E3 = A_IN + G / 4 * BS;
constexpr uint32_t A_WHS = A_PT - 128;
constexpr int SMEM = A_END - sb;
static_assert(SMEM <= 232448 && A_TAB % 1024 == 0 && A_IN % 1024 == 0 && A_PT % 1024 == 0 && A_WD2 % 128 == 0 && A_ROWS % 16 == 0, "smem");
constexpr int NX = 384, CH = NX * 16;
constexpr uint32_t A_QS = A_RING, A_W = A_QS + 49152, A_SA = A_IN, A_SB = A_SA + (G + 1) * 128, A_SRC = A_TAB;
__host__ __device__ constexpr uint32_t a_dst(int k) { return k < 2 ? A_W + 16384 + k * CH : A_SRC + (k + 2) * CH; }
static_assert(a_dst(1) + CH <= A_PT && a_dst(3) + CH <= A_IN && A_SB + (G + 1) * 256 <= A_WD, "staging");
constexpr uint32_t BAR_C = A_BAR, BAR_T = BAR_C + 64, BAR_W = A_BAR + 112, BAR_U = A_BAR + 120, BAR_Q = A_BAR + 128, BAR_X = A_BAR + 136, BAR_A = A_BAR + 144;

#define ABL 0
#define VAR 1056
#define HW0 4
constexpr int NREP = 8;
struct Scratch {
  uint4 q[(G * 384 + 64) * 8];
  uint4 x[G * G * 24];
  uint2 xe[G * G * 32];
  uint32_t wh[128 * 32];
  uint32_t ep[G * 32];
  uint32_t cnt[NREP * 32];
};
__device__ __align__(256) Scratch g_s;
#define STAMP(k)

struct Maps { CUtensorMap m[7]; };
constexpr int TM_H = 0, TM_WE = 128, TM_WH = 256, TM_Q = 384, TM_XA = 512, TM_XB = 640, TM_W3 = 768;
struct Params {
  const int* dst; const int* src; int E, EPC, force_slow, NPC; Scratch* s; int N; uint32_t magic;
  const uint16_t* h; const uint16_t* pos; const uint16_t* ea; const uint16_t* we; const uint16_t* wx; const uint16_t* wh; uint16_t* out;
  uint32_t EPC4, sched[16];
};

#define R32(d) "+f"(d[0]),"+f"(d[1]),"+f"(d[2]),"+f"(d[3]),"+f"(d[4]),"+f"(d[5]),"+f"(d[6]),"+f"(d[7]),"+f"(d[8]),"+f"(d[9]),"+f"(d[10]),"+f"(d[11]),"+f"(d[12]),"+f"(d[13]),"+f"(d[14]),"+f"(d[15]),"+f"(d[16]),"+f"(d[17]),"+f"(d[18]),"+f"(d[19]),"+f"(d[20]),"+f"(d[21]),"+f"(d[22]),"+f"(d[23]),"+f"(d[24]),"+f"(d[25]),"+f"(d[26]),"+f"(d[27]),"+f"(d[28]),"+f"(d[29]),"+f"(d[30]),"+f"(d[31])
#define S32 "{%0,%1,%2,%3,%4,%5,%6,%7,%8,%9,%10,%11,%12,%13,%14,%15,%16,%17,%18,%19,%20,%21,%22,%23,%24,%25,%26,%27,%28,%29,%30,%31}"
#define R16(d) "+f"(d[0]),"+f"(d[1]),"+f"(d[2]),"+f"(d[3]),"+f"(d[4]),"+f"(d[5]),"+f"(d[6]),"+f"(d[7]),"+f"(d[8]),"+f"(d[9]),"+f"(d[10]),"+f"(d[11]),"+f"(d[12]),"+f"(d[13]),"+f"(d[14]),"+f"(d[15])
#define S16 "{%0,%1,%2,%3,%4,%5,%6,%7,%8,%9,%10,%11,%12,%13,%14,%15}"
#define DI __device__ __forceinline__

constexpr uint64_t DHI = (64ull << 32) | (1ull << 62);
template<int SD> DI void ss64(float (&d)[32], uint64_t da, uint64_t db) {
  asm volatile("wgmma.mma_async.sync.aligned.m64n64k16.f32.bf16.bf16 " S32 ", %32, %33, %34, 1, 1, 0, 1;" : R32(d) : "l"(da), "l"(db), "n"(SD)); }
template<int SD> DI void rs64(float (&d)[32], const uint32_t* a, uint64_t db) {
  asm volatile("wgmma.mma_async.sync.aligned.m64n64k16.f32.bf16.bf16 " S32 ", {%32,%33,%34,%35}, %36, %37, 1, 1, 1;" : R32(d) : "r"(a[0]), "r"(a[1]), "r"(a[2]), "r"(a[3]), "l"(db), "n"(SD)); }
template<int SD> DI void rh64(float (&d)[32], const uint32_t* a, uint64_t db) {
  asm volatile("wgmma.mma_async.sync.aligned.m64n64k16.f32.f16.f16 " S32 ", {%32,%33,%34,%35}, %36, %37, 1, 1, 1;" : R32(d) : "r"(a[0]), "r"(a[1]), "r"(a[2]), "r"(a[3]), "l"(db), "n"(SD)); }
DI void wg_fence() { asm volatile("wgmma.fence.sync.aligned;" ::: "memory"); }
DI void wg_commit() { asm volatile("wgmma.commit_group.sync.aligned;" ::: "memory"); }
DI void wg_wait0() { asm volatile("wgmma.wait_group.sync.aligned 0;" ::: "memory"); }
DI void fence_regs(float (&d)[32]) { asm volatile("" : R32(d) :: "memory"); }
DI void fence_regs(float (&d)[16]) { asm volatile("" : R16(d) :: "memory"); }
DI void proxy_fence() { asm volatile("fence.proxy.async.shared::cta;" ::: "memory"); }
DI void hmma(uint32_t& d0, uint32_t& d1, const uint32_t* a, uint32_t b0, uint32_t b1) {
  asm("mma.sync.aligned.m16n8k16.row.col.f16.f16.f16.f16 {%0,%1}, {%2,%3,%4,%5}, {%6,%7}, {%0,%1};" : "+r"(d0), "+r"(d1) : "r"(a[0]), "r"(a[1]), "r"(a[2]), "r"(a[3]), "r"(b0), "r"(b1)); }
DI uint64_t pol_first() { uint64_t r; asm("createpolicy.fractional.L2::evict_first.b64 %0, 1.0;" : "=l"(r)); return r; }
DI float tanh_ap(float x) { float y; asm("tanh.approx.f32 %0, %1;" : "=f"(y) : "f"(x)); return y; }
DI float silu(float y) { return fmaf(y, tanh_ap(y), y); }
DI uint32_t pack_bf16(float lo, float hi) { uint32_t r; asm("cvt.rn.bf16x2.f32 %0, %1, %2;" : "=r"(r) : "f"(hi), "f"(lo)); return r; }
DI uint32_t pack_f16(float lo, float hi) { uint32_t r; asm("cvt.rn.f16x2.f32 %0, %1, %2;" : "=r"(r) : "f"(hi), "f"(lo)); return r; }
DI float bf_lo(uint32_t v) { return __uint_as_float(v << 16); }
DI float bf_hi(uint32_t v) { return __uint_as_float(v & 0xFFFF0000u); }
DI uint32_t b2h(uint32_t v) { return pack_f16(bf_lo(v), bf_hi(v)); }
DI uint32_t h2b(uint32_t v) { const float2 f = __half22float2(*(const __half2*)&v); return pack_bf16(f.x, f.y); }
DI uint32_t hadd(uint32_t a, uint32_t b) { uint32_t r; asm("add.rn.f16x2 %0, %1, %2;" : "=r"(r) : "r"(a), "r"(b)); return r; }
DI uint32_t hsub(uint32_t a, uint32_t b) { uint32_t r; asm("sub.rn.f16x2 %0, %1, %2;" : "=r"(r) : "r"(a), "r"(b)); return r; }
DI uint32_t hfma(uint32_t a, uint32_t b, uint32_t c) { uint32_t r; asm("fma.rn.f16x2 %0, %1, %2, %3;" : "=r"(r) : "r"(a), "r"(b), "r"(c)); return r; }
DI uint32_t hsilu(uint32_t y) { uint32_t t; asm("tanh.approx.f16x2 %0, %1;" : "=r"(t) : "r"(y)); return hfma(y, t, y); }
DI uint32_t badd(uint32_t a, uint32_t b) { uint32_t r; asm("add.rn.bf16x2 %0, %1, %2;" : "=r"(r) : "r"(a), "r"(b)); return r; }
DI uint32_t bhalf(uint32_t v) { uint32_t r; asm("mul.rn.bf16x2 %0, %1, %2;" : "=r"(r) : "r"(v), "r"(0x3F003F00u)); return r; }
DI uint32_t amax2(uint32_t mx, uint32_t v) { return __vmaxu2(mx, v & 0x7FFF7FFFu); }
DI uint32_t amax_warp(uint32_t mx) { return __reduce_max_sync(~0u, max(mx & 0xFFFF, mx >> 16)); }
DI uint32_t decode(uint32_t a, uint32_t b, uint32_t c, uint32_t d) {
  if (XD) return a ^ __funnelshift_l(b, b, 2) ^ __funnelshift_l(c, c, 4) ^ __funnelshift_l(d, d, 6);
  return a + b * 4 + c * 16 + d * 64;
}
DI void mbar_wait(uint32_t bar, uint32_t parity) {
  asm volatile("{.reg .pred p; .reg .u32 c; mov.u32 c, 0;\n"
    "LW_%=: mbarrier.try_wait.parity.shared::cta.b64 p, [%0], %1;\n"
    "@p bra.uni LD_%=;\n add.u32 c, c, 1; setp.lt.u32 p, c, 20000000;\n @p bra.uni LW_%=;\n LD_%=:}" :: "r"(bar), "r"(parity) : "memory");
}
DI void mbar_arrive(uint32_t bar) { asm volatile("mbarrier.arrive.shared::cta.b64 _, [%0];" :: "r"(bar) : "memory"); }
DI void bar_sync(int id, int n) { asm volatile("bar.sync %0, %1;" :: "r"(id), "r"(n) : "memory"); }
DI void bar_arrive(int id, int n) { asm volatile("bar.arrive %0, %1;" :: "r"(id), "r"(n) : "memory"); }
DI void sts128(uint32_t a, uint32_t x, uint32_t y, uint32_t z, uint32_t w) { asm volatile("st.shared.v4.u32 [%0], {%1,%2,%3,%4};" :: "r"(a), "r"(x), "r"(y), "r"(z), "r"(w) : "memory"); }
DI void sts64(uint32_t a, uint32_t x, uint32_t y) { asm volatile("st.shared.v2.u32 [%0], {%1,%2};" :: "r"(a), "r"(x), "r"(y) : "memory"); }
DI void sts32(uint32_t a, uint32_t x) { asm volatile("st.shared.u32 [%0], %1;" :: "r"(a), "r"(x) : "memory"); }
DI void sts16(uint32_t a, uint32_t x) { asm volatile("st.shared.u16 [%0], %1;" :: "r"(a), "h"((uint16_t)x) : "memory"); }
DI void sts32p(uint32_t a, uint32_t x, bool p) { asm volatile("{.reg .pred p; setp.ne.b32 p, %2, 0; @p st.shared.u32 [%0], %1;}" :: "r"(a), "r"(x), "r"((int)p) : "memory"); }
DI void sts16p(uint32_t a, uint32_t x, bool p) { asm volatile("{.reg .pred p; setp.ne.b32 p, %2, 0; @p st.shared.u16 [%0], %1;}" :: "r"(a), "h"((uint16_t)x), "r"((int)p) : "memory"); }
DI void lds128(uint32_t* v, uint32_t a) { asm volatile("ld.shared.v4.u32 {%0, %1, %2, %3}, [%4];" : "=r"(v[0]), "=r"(v[1]), "=r"(v[2]), "=r"(v[3]) : "r"(a) : "memory"); }
DI void lds64(uint32_t& x, uint32_t& y, uint32_t a) { asm volatile("ld.shared.v2.u32 {%0, %1}, [%2];" : "=r"(x), "=r"(y) : "r"(a) : "memory"); }
DI uint32_t lds32(uint32_t a) { uint32_t x; asm volatile("ld.shared.u32 %0, [%1];" : "=r"(x) : "r"(a) : "memory"); return x; }
DI uint32_t lds16(uint32_t a) { uint32_t x; asm volatile("ld.shared.u16 %0, [%1];" : "=r"(x) : "r"(a) : "memory"); return x; }
DI uint32_t atoms_add(uint32_t a, uint32_t v) { uint32_t r; asm volatile("atom.shared.add.u32 %0, [%1], %2;" : "=r"(r) : "r"(a), "r"(v) : "memory"); return r; }
DI uint32_t atoms_incp(uint32_t a, bool p) { uint32_t r = 0; asm volatile("{.reg .pred p; setp.ne.b32 p, %2, 0; @p atom.shared.add.u32 %0, [%1], 1;}" : "+r"(r) : "r"(a), "r"((int)p) : "memory"); return r; }
DI uint32_t ldg_poll(const void* a) { uint32_t x; asm volatile("ld.relaxed.gpu.global.u32 %0, [%1];" : "=r"(x) : "l"(a) : "memory"); return x; }
DI uint2 ldg_poll2(const void* a) { uint2 x; asm volatile("ld.relaxed.gpu.global.v2.u32 {%0, %1}, [%2];" : "=r"(x.x), "=r"(x.y) : "l"(a) : "memory"); return x; }
DI void bulk_load(uint32_t dst, const void* src, uint32_t bytes, uint32_t bar) {
  asm volatile("cp.async.bulk.shared::cluster.global.mbarrier::complete_tx::bytes.L2::cache_hint [%0], [%1], %2, [%3], %4;" :: "r"(dst), "l"(src), "r"(bytes), "r"(bar), "l"(pol_first()) : "memory"); }
DI void mbar_expect(uint32_t bar, uint32_t bytes) { asm volatile("mbarrier.arrive.expect_tx.shared::cta.b64 _, [%0], %1;" :: "r"(bar), "r"(bytes) : "memory"); }
DI void mbar_init(uint32_t bar, int n) { asm volatile("mbarrier.init.shared::cta.b64 [%0], %1;" :: "r"(bar), "r"(n) : "memory"); }
DI void tma_load(uint32_t dst, uint64_t tm, int row, uint32_t bar) {
  asm volatile("cp.async.bulk.tensor.2d.shared::cluster.global.mbarrier::complete_tx::bytes.L2::cache_hint [%0], [%1, {%3, %4}], [%2], %5;" :: "r"(dst), "l"(tm), "r"(bar), "r"(0), "r"(row), "l"(pol_first()) : "memory"); }
DI void tma_store(uint64_t tm, int col, int row, uint32_t src) {
  asm volatile("cp.async.bulk.tensor.2d.global.shared::cta.bulk_group [%0, {%2, %3}], [%1];" :: "l"(tm), "r"(src), "r"(col), "r"(row) : "memory"); }
DI void bulk_commit() { asm volatile("cp.async.bulk.commit_group;" ::: "memory"); }
DI void stsm4(uint32_t a, uint32_t x, uint32_t y, uint32_t z, uint32_t w) { asm volatile("stmatrix.sync.aligned.m8n8.x4.shared.b16 [%0], {%1,%2,%3,%4};" :: "r"(a), "r"(x), "r"(y), "r"(z), "r"(w) : "memory"); }
DI void ldsm4(uint32_t* v, uint32_t a) { asm volatile("ldmatrix.sync.aligned.m8n8.x4.shared.b16 {%0,%1,%2,%3}, [%4];" : "=r"(v[0]), "=r"(v[1]), "=r"(v[2]), "=r"(v[3]) : "r"(a) : "memory"); }
DI void ldsm4t(uint32_t& x, uint32_t& y, uint32_t& z, uint32_t& w, uint32_t a) { asm volatile("ldmatrix.sync.aligned.m8n8.x4.trans.shared.b16 {%0,%1,%2,%3}, [%4];" : "=r"(x), "=r"(y), "=r"(z), "=r"(w) : "r"(a) : "memory"); }

__device__ __noinline__ void slow_path(const Params& p) {
  const int lane = threadIdx.x & 31, wid = threadIdx.x >> 5;
  const uint32_t ab = sb + wid * (24 * 528);
  const uint32_t* we = (const uint32_t*)p.we;
  const int nend = min(p.N, (blockIdx.x + 1) * p.NPC);
  auto rowmul = [&](uint32_t hv, const uint32_t* w, float& y0, float& y1) {
#pragma unroll 4
    for (int k = 0; k < 32; k++) {
      const uint32_t hk = __shfl_sync(~0u, hv, k), wa = __ldg(w + 2 * k * 32 + lane), wb = __ldg(w + (2 * k + 1) * 32 + lane);
      y0 = fmaf(bf_lo(hk), bf_lo(wa), fmaf(bf_hi(hk), bf_lo(wb), y0)); y1 = fmaf(bf_lo(hk), bf_hi(wa), fmaf(bf_hi(hk), bf_hi(wb), y1));
    }
  };
  auto act = [](float x) { return x / (1.f + __expf(-x)); };
  auto hrow = [&](int n) { return __ldg(p.h + (size_t)n * 64 + 2 * lane) | ((uint32_t)__ldg(p.h + (size_t)n * 64 + 2 * lane + 1) << 16); };
  const uint32_t wdv = __ldg(we + 128 * 32 + lane), wxv = __ldg((const uint32_t*)p.wx + lane);
  for (int nb = blockIdx.x * p.NPC + wid * 24; nb < nend; nb += 384) {
    const int cnt = min(24, nend - nb);
    for (int n = 0; n < cnt; n++) {
      float y0 = 0.f, y1 = 0.f; rowmul(hrow(nb + n), we, y0, y1);
      sts64(ab + n * 528 + lane * 8, 0, 0); sts64(ab + n * 528 + 256 + lane * 8, __float_as_uint(y0), __float_as_uint(y1));
      if (lane < 4) sts32(ab + n * 528 + 512 + lane * 4, 0);
    }
    __syncwarp();
    for (int base = 0; base < p.E; base += 32) {
      const uint32_t dl = base + lane < p.E ? (uint32_t)(__ldg(p.dst + base + lane) - nb) : 0xFFFFFFFFu;
      uint32_t mk = __ballot_sync(~0u, dl < (uint32_t)cnt);
      while (mk) {
        const int l = __ffs(mk) - 1; mk &= mk - 1;
        const int e = base + l, n = __shfl_sync(~0u, dl, l), s = __ldg(p.src + e);
        const uint32_t a = ab + n * 528;
        float df = 0.f;
        if (lane < 3) df = bf_lo(pack_bf16(bf_lo(__ldg(p.pos + (size_t)(nb + n) * 3 + lane)) - bf_lo(__ldg(p.pos + (size_t)s * 3 + lane)), 0.f));
        float d2 = df * df; d2 += __shfl_xor_sync(~0u, d2, 1); d2 += __shfl_xor_sync(~0u, d2, 2); d2 = __shfl_sync(~0u, d2, 0);
        uint32_t x0, x1; lds64(x0, x1, a + 256 + lane * 8);
        float y0 = fmaf(d2, bf_lo(wdv), __uint_as_float(x0)), y1 = fmaf(d2, bf_hi(wdv), __uint_as_float(x1));
        rowmul(hrow(s), we + 64 * 32, y0, y1);
        for (int k = 0; k < 16; k++) { const float ev = bf_lo(__ldg(p.ea + (size_t)e * 16 + k)); const uint32_t w = __ldg(we + (129 + k) * 32 + lane); y0 = fmaf(ev, bf_lo(w), y0); y1 = fmaf(ev, bf_hi(w), y1); }
        y0 = act(y0); y1 = act(y1);
        float c = y0 * bf_lo(wxv) + y1 * bf_hi(wxv);
#pragma unroll
        for (int o = 16; o; o >>= 1) c += __shfl_xor_sync(~0u, c, o);
        lds64(x0, x1, a + lane * 8);
        sts64(a + lane * 8, __float_as_uint(__uint_as_float(x0) + y0), __float_as_uint(__uint_as_float(x1) + y1));
        if (lane < 3) sts32(a + 512 + lane * 4, __float_as_uint(fmaf(c, df, __uint_as_float(lds32(a + 512 + lane * 4)))));
      }
    }
    __syncwarp();
    for (int n = 0; n < cnt; n++) {
      const uint32_t hv = hrow(nb + n); uint32_t x0, x1; lds64(x0, x1, ab + n * 528 + lane * 8);
      float y0 = 0.f, y1 = 0.f; rowmul(hv, (const uint32_t*)p.wh, y0, y1); rowmul(pack_bf16(__uint_as_float(x0), __uint_as_float(x1)), (const uint32_t*)p.wh + 64 * 32, y0, y1);
      const uint32_t o = badd(hv, pack_bf16(act(y0), act(y1)));
      p.out[(size_t)(nb + n) * 64 + 2 * lane] = (uint16_t)o; p.out[(size_t)(nb + n) * 64 + 2 * lane + 1] = (uint16_t)(o >> 16);
      if (lane < 3) p.out[(size_t)p.N * 64 + (size_t)(nb + n) * 3 + lane] = (uint16_t)pack_bf16(bf_lo(__ldg(p.pos + (size_t)(nb + n) * 3 + lane)) + __uint_as_float(lds32(ab + n * 528 + 512 + lane * 4)), 0.f);
    }
    __syncwarp();
  }
}

__global__ void __launch_bounds__(NT, 1) egnn_kernel(const __grid_constant__ Params p, const __grid_constant__ Maps maps) {
  extern __shared__ __align__(1024) unsigned char smraw[];
  const int tid = threadIdx.x, cta = blockIdx.x;
  const int e0 = cta * p.EPC, nb = max(0, min(p.EPC, p.E - e0)) * 4;
  STAMP(0);
  auto load_idx = [&](int c) {
    const int o = (c & 3) * CH, n = max(0, min(CH, nb - o));
    mbar_expect(BAR_C + c * 8, n);
    if (n) bulk_load(c < 4 ? a_dst(c) : A_SRC + o, (const char*)((c < 4 ? p.dst : p.src) + e0) + o, n, BAR_C + c * 8);
  };
  if (tid == 480 && !p.force_slow) {
#pragma unroll
    for (int c = 0; c < 4; c++) mbar_init(BAR_C + c * 8, 1);
    asm volatile("fence.mbarrier_init.release.cluster;" ::: "memory");
#pragma unroll
    for (int c = 0; c < 4; c++) load_idx(c);
  }
  if ((uint32_t)__cvta_generic_to_shared(smraw) != sb) return;
  if (p.force_slow) { slow_path(p); return; }
  uint32_t ep = ldg_poll(p.s->ep + cta * 32), tgb;
  const uint64_t tmb = (uint64_t)&maps;
  const int lane = tid & 31, wid = __shfl_sync(~0u, tid >> 5, 0), g8 = lane >> 2, q = lane & 3;
  uint32_t whx = 0;
  if (wid >= 12) {
    if (wid == 15) asm volatile("ld.global.nc.u32 %0, [%1];" : "=r"(whx) : "l"((const uint32_t*)p.wh + (cta & 127) * 32 + lane));
    if (tid == 480 || tid == 448) {
#pragma unroll
      for (int c = 0; c < 10; c++) if (tid == 480 || c < 5) mbar_init(BAR_C + (tid == 480 ? 32 : 112) + c * 8, tid == 448 && c == 4 ? 16 : 1);
      asm volatile("fence.mbarrier_init.release.cluster;" ::: "memory");
    }
    if (tid - 416 < 7u) asm volatile("prefetch.tensormap [%0];" :: "l"(tmb + (tid - 416) * 128));
    __syncwarp();
    if (wid == 15) bar_arrive(7, NT); else bar_sync(7, NT);
    if (tid == 480) {
#pragma unroll 1
      for (int c = 4; c < 14; c++) {
        if (c >= WIN) mbar_wait(BAR_C + (c < 8 ? c - WIN : HW0) * 8, 0);
        if (c < 8) load_idx(c); else { mbar_expect(BAR_C + c * 8, 8192); tma_load(A_PT + (c - 8) * 8192, tmb + TM_H, cta * p.NPC + (c - 8) * 64, BAR_C + c * 8); }
      }
    }
    if (tid == 448) {
      mbar_expect(BAR_W, 2 * 8192 + 2048 + 256);
      tma_load(A_W, tmb + TM_WE, 64, BAR_W); tma_load(A_W + 8192, tmb + TM_WE, 0, BAR_W); tma_load(A_W3, tmb + TM_W3, 129, BAR_W);
      bulk_load(A_WD, p.we + 128 * 64, 128, BAR_W); bulk_load(A_WD + 128, p.wx, 128, BAR_W);
    }
    __syncwarp();
  }

  const int w = wid & 3;
  const uint32_t frag = (w * 16 + (lane & 15)) * 128 + (((lane >> 4) ^ (lane & 7)) << 4), pa = A_POSH + (w * 16 + g8) * 8 + q * 2;
  float a0[32], a1[32];
  float mx = 0.f;
  auto mma = [&](float (&acc)[32], int b, int blk) {
    const uint64_t da = DHI | ((A_PT + blk * 8192) >> 4), db = DHI | ((A_W + b * 8192) >> 4);
    wg_fence();
    ss64<0>(acc, da, db); ss64<1>(acc, da + 2, db + 128); ss64<1>(acc, da + 4, db + 256); ss64<1>(acc, da + 6, db + 384);
    wg_commit();
  };
  auto epi = [&](float (&acc)[32], int b, int blk) {
    uint32_t o[16];
#pragma unroll
    for (int j = 0; j < 16; j++) o[j] = pack_f16(acc[2 * j], acc[2 * j + 1]);
    if (b) {
#pragma unroll
      for (int j = 0; j < 32; j++) mx = fmaxf(mx, fabsf(acc[j]));
    } else {
#pragma unroll
      for (int r = 0; r < 2; r++) {
        const uint32_t T = __byte_perm(lds16(pa + blk * 512 + r * 64), 0, 0x4140);
#pragma unroll
        for (int j = 0; j < 4; j++) o[2 * j + r] &= 0xFFFCFFFCu;
        const uint32_t S = decode(o[r], o[2 + r], o[4 + r], o[6 + r]);
        const uint32_t X = (T - S) & 255, Y = XD ? S ^ T : X | ((T - ((S + X) & 0xFFFF0000u)) & 0x00FF0000u);
#pragma unroll
        for (int j = 0; j < 4; j++) o[2 * j + r] |= (Y >> (2 * j)) & 0x00030003u;
      }
    }
    const uint32_t a = (b ? A_PT : A_QS) + blk * 8192 + frag;
#pragma unroll
    for (int j = 0; j < 4; j++) stsm4(a ^ (j << 5), o[4 * j], o[4 * j + 1], o[4 * j + 2], o[4 * j + 3]);
  };
  uint32_t W3[16], PB[16], WX[8];
  auto frags = [&]() {
#pragma unroll
    for (int k = 0; k < 4; k++) ldsm4t(W3[4 * k], W3[4 * k + 1], W3[4 * k + 2], W3[4 * k + 3], A_W3 + (lane & 15) * 128 + ((((lane >> 4) + 2 * k) ^ (lane & 7)) << 4));
#pragma unroll
    for (int j = 0; j < 8; j++) WX[j] = lds32(A_WD + 128 + j * 16 + q * 4);
  };
  auto p_check = [&](int blk) {
    const uint32_t pm = __reduce_max_sync(~0u, __float_as_uint(mx));
    if (pm > 0x46000000u || (pm < 0x3A800000u && blk * 64 + (w + 1) * 16 <= min(p.NPC, p.N - cta * p.NPC))) sts32(A_MISC, 1);
  };
  if (wid >= 12) {
    const int node0 = cta * p.NPC, nloc = max(0, min(p.NPC, p.N - node0));
    if (w == 3) {
      const uint32_t mh = amax_warp(whx & 0x7FFF7FFFu);
      sts32(A_WHS + lane * 4, cta < 64 ? bhalf(whx) : mh && mh < 0x3B00 ? ~0u : b2h(bhalf(whx)));
      __syncwarp();
      if (lane == 0 && cta < 128) { proxy_fence(); asm volatile("cp.async.bulk.global.shared::cta.bulk_group [%0], [%1], 128;" :: "l"(p.s->wh + cta * 32), "r"(A_WHS) : "memory"); }
      __syncwarp();
      ep++;
    }
    else {
      const int t = tid - 384;
      uint32_t ps[12], mp = 0;
#pragma unroll
      for (int k = 0; k < 4; k++) {
        ps[3 * k] = ps[3 * k + 1] = ps[3 * k + 2] = 0;
        asm volatile("{.reg .pred p; setp.lt.s32 p, %4, %5;\n @p ld.global.nc.u16 %0, [%3];\n @p ld.global.nc.u16 %1, [%3+2];\n @p ld.global.nc.u16 %2, [%3+4];}"
          : "+r"(ps[3 * k]), "+r"(ps[3 * k + 1]), "+r"(ps[3 * k + 2]) : "l"(p.pos + (size_t)(node0 + t + 96 * k) * 3), "r"(t + 96 * k), "r"(p.N - node0));
      }
      mbar_wait(BAR_W, 0);
#pragma unroll
      for (int k = 0; k < 11; k++) if (k < 10 || w < 2) { uint32_t v[4]; const uint32_t a = A_W + (t + k * 96) * 16; lds128(v, a); sts128(a, bhalf(v[0]), bhalf(v[1]), bhalf(v[2]), bhalf(v[3])); }
      const uint32_t wd = lds32(A_WD + lane * 4), md = amax_warp(wd & 0x7FFF7FFFu);
      bool bad = md - 0x3B00 > 0x680;
      if (w < 2) {
        uint32_t mw = 0;
#pragma unroll
        for (int k = 0; k < 2; k++) { uint32_t v[4]; const uint32_t a = A_W3 + (t + k * 64) * 16; lds128(v, a);
          sts128(a, b2h(bhalf(v[0])), b2h(bhalf(v[1])), b2h(bhalf(v[2])), b2h(bhalf(v[3]))); mw = amax2(amax2(amax2(amax2(mw, v[0]), v[1]), v[2]), v[3]); }
        bad |= amax_warp(mw) - 0x3B00 > 0x680;
      } else {
#pragma unroll
        for (int r = 0; r < 8; r++) sts32(A_WD2 + r * 128 + ((lane * 4) ^ (r << 4)), (r & 1) ? 0 : r == 6 ? 0xF753F753u : b2h(bhalf(wd)));
        const uint32_t x = lds32(A_WD + 128 + lane * 4), ex = min(max(amax_warp(x & 0x7FFF7FFFu) >> 7, 20u), 230u);
        const float sc = __uint_as_float((252 - ex) << 23);
        sts32(A_WD + 128 + lane * 4, pack_f16(bf_lo(x) * sc, bf_hi(x) * sc)); sts32(A_MISC + 12, (ex + 2) << 23);
      }
#pragma unroll
      for (int k = 0; k < 4; k++) {
        const int n = t + 96 * k;
        sts64(A_POSH + n * 8, pack_f16(bf_lo(ps[3 * k]), bf_lo(ps[3 * k + 1])), pack_f16(bf_lo(ps[3 * k + 2]), 1.f));
        sts16(A_POSB + n * 6, ps[3 * k]); sts16(A_POSB + n * 6 + 2, ps[3 * k + 1]); sts16(A_POSB + n * 6 + 4, ps[3 * k + 2]);
        mp = amax2(amax2(mp, ps[3 * k] | (ps[3 * k + 1] << 16)), ps[3 * k + 2]);
      }
      mp = amax_warp(mp);
      if (bad || !(bf_lo(mp) * bf_lo(mp) * bf_lo(md) < 6000.f) || (mp < 0x3B80 && (w + 1) * 32 <= nloc)) sts32(A_MISC, 1);
      proxy_fence();
      if (w == 0) STAMP(16);
      bar_arrive(3, NX + 96);
      ep++;
    }
    bar_sync(6, 128);
#pragma unroll 1
    for (int blk = T3; blk < 6; blk = max(blk + 1, 4)) {
      mbar_wait(BAR_T + blk * 8, 0);
      if (w == 0 && blk == 5) STAMP(17);
      mma(a0, 0, blk); mma(a1, 1, blk);
      asm volatile("wgmma.wait_group.sync.aligned 1;" ::: "memory"); fence_regs(a0);
      epi(a0, 0, blk);
      wg_wait0(); fence_regs(a1);
      bar_sync(6, 128);
      if (w == 3 && blk == 5) {
        bar_sync(8, NX + 32);
        if (lane == 0) {
          proxy_fence();
#pragma unroll 1
          for (int b = 0; b * 64 < nloc; b++) tma_store(tmb + TM_Q, 0, node0 + b * 64, A_QS + b * 8192);
          STAMP(18);
        }
        __syncwarp();
      }
      epi(a1, 1, blk);
    }
    p_check(T3);
    frags();
    tgb = ep << 31;
  } else {
    if (tid < (A_CNT - A_MISC) / 16) sts128(A_MISC + tid * 16, 0, tid == 0 ? 16 : 0, 0, 0);
    const uint32_t acnt = A_CNT + ((tid + cta * p.NPC) & 511) * 4;
    sts32(acnt, A_TAB + tid * (CAP * 2));
    if (tid < 32) sts32(A_CNT + 2048 + tid * 4, A_TRASH);
    ep++; tgb = ep << 31;
    const uint32_t tga = (ep & 63) * 0x04000400u, tgh = tga & 0xFFFF0000u;
    {
      const uint32_t x = tga + (512 + (tid & 7) * 4) * 0x10001u;
#pragma unroll
      for (int k = 0; k < 3; k++) if (k < 2 || tid < (G + 1) * 8 - 2 * NX) {
        const uint32_t i = tid + k * NX, hw = ((i >> 3) & 31) - (i & 7) * 4;
        sts128(A_SA + i * 16, x, x + 0x10001u, x + 0x20002u, x + 0x30003u);
        sts32p(A_SA + i * 16 + hw * 4, tgh + (i & 7) * 16 + hw * 4 + 4, hw < 4);
      }
#pragma unroll
      for (int k = 0; k < 6; k++) if (k < 5 || tid < G * 16 - 5 * NX) sts128(A_SB + (tid + k * NX) * 16, tgb, tgb, tgb, tgb);
    }
    bar_sync(7, NT);
    STAMP(23);
    uint32_t d[16], oo[16], xx[16], lc[16], mxx = 0;
#pragma unroll
    for (int c = 0; c < 4; c++) {
      mbar_wait(BAR_C + c * 8, 0);
      if (c == 3) STAMP(1);
      lds128(d + 4 * c, a_dst(c) + tid * 16);
#pragma unroll
      for (int k = 4 * c; k < 4 * c + 4; k++) {
        if (tid * 16 + c * CH >= nb) d[k] = G * p.NPC;
        const uint32_t j = __umulhi(d[k], p.magic);
        xx[k] = atoms_add(A_SA + (j * 128 | ((j * 4) & 0x7C)), 258);
        oo[k] = j * 128;
      }
    }
#pragma unroll
    for (int k = 0; k < 16; k++) { oo[k] |= xx[k] & 0x7E; mxx = max(mxx, xx[k]); }
    if (mxx > tgh + 15900) {
#pragma unroll
      for (int k = 0; k < 16; k++) if (xx[k] > tgh + 15900) oo[k] = G * 128 + 64 + lane * 2;
    }
#pragma unroll
    for (int k = 0; k < 16; k++) sts16(A_SA + oo[k], (d[k] & 511) | tga);
    if (wid == 0) { bar_sync(1, NX); if (lane == 0) { proxy_fence(); tma_store(tmb + TM_XA, cta * 192, 0, A_SA); bulk_commit(); } __syncwarp(); } else bar_arrive(1, NX);
    STAMP(2);
    const uint32_t eb = tgb + ((tid * 4 + (cta & 3) * p.EPC) << 16);
#pragma unroll
    for (int c = 0; c < 4; c++) {
      mbar_wait(BAR_C + 32 + c * 8, 0);
      if (wid == 0 && c == 3) STAMP(21);
      lds128(lc + 4 * c, A_SRC + c * CH + tid * 16);
#pragma unroll
      for (int k = 4 * c; k < 4 * c + 4; k++) { lc[k] += eb + ((c * NX * 4 + (k & 3)) << 16); sts32(A_SB + oo[k] * 2, lc[k]); }
    }
    bar_sync(2, NX);
    if (tid == 0) { proxy_fence(); tma_store(tmb + TM_XB, cta * 96 + 32, 0, A_SB); bulk_commit(); p.s->ep[cta * 32] = ep; }
    __syncwarp();
    STAMP(3);
    if (mxx > tgh + 15900) {
#pragma unroll
      for (int k = 0; k < 16; k++) {
        const uint32_t j = __umulhi(d[k], p.magic), r = (xx[k] - tgh) / 258 - 62;
        if (r < 31 && j < G)
          asm volatile("st.relaxed.gpu.global.v2.u32 [%0], {%1, %2};" :: "l"(p.s->xe + (j * G + cta) * 32 + r), "r"(lc[k]), "r"((d[k] & 511) | (ep << 9)) : "memory");
      }
    }
    __syncwarp();
    constexpr int JS = 12; const int j0 = wid;
#pragma unroll
    for (int k = 0; k < 7; k++) if (k < 6 || tid < 385 * CAP / 8 + 9 - 6 * NX) sts128(A_TAB + (tid + k * NX) * 16, 0, 0, 0, 0);
    bar_sync(3, NX + 96);
    STAMP(12);
    const char* xin = (const char*)(p.s->x + cta * G * 24);
    uint32_t pk[11];
    const uint32_t rot = (lane + cta) & 31;
    auto poll_a = [&]() {
#pragma unroll
      for (int k = 0; k < 11; k++) pk[k] = ldg_poll(xin + (j0 + JS * k) * FS + rot * 4);
    };
    uint32_t xs = ~0u; uint2 xv;
    const uint32_t t0 = (wid >> 2) * BS + 128 + w * 256 + rot * 8, tx = lane ? tga : tgh;
    const uint32_t h1 = (cta & 31) * 4 + 4 + 62 * 258;
    int spin = 0;
    auto copy_b = [&]() {
      const uint32_t o = (j0 + JS * (lane >> 4)) * FS + 128 + (lane & 15) * 16, a = A_IN + ((wid >> 2) + 3 * (lane >> 4)) * BS + 128 + w * 256 + (lane & 15) * 16;
#pragma unroll
      for (int k = 0; k < 6; k++) if (k < 5 || lane < 16)
        asm volatile("cp.async.cg.shared.global.L2::cache_hint [%0], [%1], 16, %2;" :: "r"(a + k * 6 * BS), "l"(xin + o + k * 2 * JS * FS), "l"(pol_first()) : "memory");
    };
    {
      const int blk = (wid >> 2) + !T3;
      mbar_wait(BAR_T + blk * 8, 0);
      if (wid == 8) STAMP(22);
      mma(a0, 0, blk); if (!PL) mma(a1, 1, blk);
      asm volatile("wgmma.wait_group.sync.aligned %0;" :: "n"(!PL) : "memory"); fence_regs(a0);
      epi(a0, 0, blk);
      bar_arrive(8, NX + 32);
      poll_a();
      if (PL) mma(a1, 1, blk);
      wg_wait0(); fence_regs(a1);
      bar_sync(13 + (wid >> 2), 128);
      epi(a1, 1, blk);
      p_check(blk);
      if (FR == 0) frags();
      if (wid == 8) STAMP(24);
    }
    {
      {
        for (;;) {
          uint32_t mh = 0, bad = 0;
#pragma unroll
          for (int k = 0; k < 11; k++) { pk[k] ^= tx; mh = max(mh, pk[k]); bad |= pk[k]; }
          if (!__any_sync(~0u, bad & (lane ? 0xFC00FC00u : 0xFC000000u))) {
            if (__shfl_sync(~0u, mh, 0) > h1) {
              uint32_t base = 0;
#pragma unroll
              for (int k = 0; k < 11; k++) {
                const uint32_t c = (max(__shfl_sync(~0u, pk[k], 0), h1) - h1) / 258;
                if (lane - base < c) xs = (j0 + JS * k) * 32 + lane - base;
                base += c;
              }
              if (base > 31) { sts32(A_MISC, 1); xs = ~0u; }
              if (xs != ~0u) xv = ldg_poll2(p.s->xe + cta * G * 32 + xs);
              __syncwarp();
            }
            break;
          }
          if (++spin > 2000000) __trap();
          poll_a();
        }
        STAMP(14); if (wid == 8) STAMP(25);
        uint32_t r0[11], r1[11];
#pragma unroll
        for (int k = 0; k < 11; k++) {
          if (lane == 0) pk[k] = (512 + rot) * 0x10001u;
          r0[k] = atoms_add(A_CNT + (pk[k] & 0xFFFF) * 4, 2);
          r1[k] = atoms_add(A_CNT + (pk[k] >> 16) * 4, 2);
        }
#pragma unroll
        for (int k = 0; k < 11; k++) { sts16(min(r0[k], A_IN - 2), t0 + 3 * k * BS); sts16(min(r1[k], A_IN - 2), t0 + 3 * k * BS + 4); }
        if (wid == 8) STAMP(26);
      }
    }
    if (tid == 0) { asm volatile("cp.async.bulk.wait_group.read 0;" ::: "memory"); mbar_arrive(BAR_X); }
    __syncwarp();
    mbar_wait(BAR_X, 0);
    copy_b();
    STAMP(4);
    if (xs != ~0u) {
      for (int i = 0; (((xv.x ^ tgb) >> 31) | ((xv.y >> 9) ^ (ep & 0x7FFFFF))) && i < 2000000; i++) xv = ldg_poll2(p.s->xe + cta * G * 32 + xs);
      const uint32_t n = atoms_add(A_XC + (xs >> 7) * 4, 4), t = (xs >> 7) * BS + 4 + min(n, 120u);
      if (n > 120) sts32(A_MISC, 1);
      sts16(min(atoms_add(A_CNT + (xv.y & 511) * 4, 2), A_IN - 2), t);
      sts32(A_IN + t, xv.x);
    }
    __syncwarp();
    if (FR == 1) frags();
    bar_sync(4, NX);
    STAMP(5);
    {
      const uint32_t dg = (lds32(acnt) - (A_TAB + tid * (CAP * 2))) >> 1;
      const uint32_t dr = atoms_add(A_DH + min(dg, 63u) * 4, 1);
      bar_sync(5, NX);
      uint32_t hb, ha; lds64(hb, ha, A_DH + (62 - 2 * lane) * 4);
      uint32_t inc = ha + hb;
#pragma unroll
      for (int o = 1; o < 32; o <<= 1) { const uint32_t y = __shfl_up_sync(~0u, inc, o); if (lane >= o) inc += y; }
      const uint32_t idx = 63 - min(dg, 63u);
      const uint32_t e2 = __shfl_sync(~0u, (inc - hb) | ((inc - hb - ha) << 16), idx >> 1);
      const uint32_t pos = ((idx & 1) ? (e2 & 0xFFFF) : (e2 >> 16)) + dr;
      sts16(A_ROWS + pos * 2, tid);
      if (!(pos & 7)) sts32(A_LEN + (pos >> 1), max(1u, (dg + 1) >> 1));
      if (dg > CAP) sts32(A_MISC, 1);
    }
    STAMP(6);
    if (tid == 0) sts32(A_IN, 0xFFFF);
    for (;;) {
      asm volatile("cp.async.wait_all;" ::: "memory");
      __syncwarp();
      uint32_t bad = 0;
#pragma unroll
      for (int k = 0; k < 11; k++) { uint32_t x, y; lds64(x, y, A_IN + t0 + 3 * k * BS); bad |= (x ^ tgb) | (y ^ tgb); }
      if (!__any_sync(~0u, bad >> 31) || ++spin > 2000000) break;
      copy_b();
    }
    if (FR == 2) frags();
    STAMP(7);
  }
  if (wid == 15) {
    bar_arrive(11, NT);
    if (lane == 0) { bulk_commit(); asm volatile("cp.async.bulk.wait_group 0;" ::: "memory"); }
    __syncwarp();
    if (lane < NREP) asm volatile("red.relaxed.gpu.global.add.u32 [%0], 1;" :: "l"(p.s->cnt + lane * 32) : "memory");
    if (lane == 0) {
      STAMP(19);
      const uint32_t nbe = (p.E / G) & ~15u;
#pragma unroll 1
      for (int i = 0; i < PFA; i++)
        if (nbe) asm volatile("cp.async.bulk.prefetch.L2.global [%0], %1;" :: "l"((const char*)p.ea + (size_t)(i * G + cta) * nbe), "r"(nbe) : "memory");
      uint32_t c; int spin = 0;
      do asm volatile("ld.acquire.gpu.global.u32 %0, [%1];" : "=r"(c) : "l"(p.s->cnt + (cta % NREP) * 32) : "memory"); while ((int)(c - ep * G) < 0 && ++spin < 20000000);
      mbar_arrive(BAR_Q);
      STAMP(20);
    }
    __syncwarp();
  }
  uint32_t A2[4];
  const uint32_t ring = 4096 + wid * 4096, ering = (wid < 8 ? 69632 : A_E3 - 8 * 1536) + wid * 1536;
  const int oc = lane >> 3;
  const int r7 = lane & 7, ro = r7 >> 1, ri = 2 * (oc & 1) + (r7 & 1);
  uint64_t qp0 = (uint64_t)p.s->q + ((r7 ^ (2 * oc)) << 4), qp1 = qp0 ^ 16, epp = (uint64_t)p.ea + (((lane ^ oc) & 1) << 4) - (tgb >> 11);
  uint32_t dq = ring + oc * 512 + r7 * 16, de = ering + ((lane * 16) ^ ((oc >> 1) * 64));
  uint32_t rq = ring + (4 * ro + ri) * 128 + (((oc >> 1) ^ r7) << 4), re = ering + ro * 128 + ((ri ^ (2 * (ro >> 1))) << 5) + ((((oc >> 1) ^ ro) & 1) << 4);
  A2[0] = (g8 >> 1) == q ? ((g8 & 1) ? 0x3C000000u : 0x3C00u) : 0;
  A2[0] += lds32(A_MISC + 8); A2[1] = A2[0] + lds32(A_MISC + 8);
  asm volatile("" : "+l"(qp0), "+l"(qp1), "+l"(epp), "+r"(dq), "+r"(de), "+r"(rq), "+r"(re));
  bar_sync(wid < 15 ? 11 : 12, wid < 15 ? NT : 64);
  if (wid == 14) bar_arrive(12, 64);
  STAMP(13);
  if (__any_sync(~0u, lds32(A_MISC))) { sts32(A_MISC + 12, dq ^ de ^ rq ^ re ^ (uint32_t)qp0 ^ (uint32_t)qp1 ^ (uint32_t)(epp ^ (epp >> 32)) ^ A2[1]); __syncthreads(); slow_path(p); return; }

  uint32_t MS[8], acc[16], m[16], yh[8], A1[4], OP, TA, D = 0, U = 0, tt, tn, rec, rn, sl;
  re += lds32(A_MISC) + 1024 - ering; de += lds32(A_MISC) + 1024 - re; const uint32_t rtop = re + lds32(A_MISC);
  uint64_t pol;
  asm("createpolicy.range.global.L2::evict_normal.L2::evict_first.b64 %0, [%1], %2, %3;" : "=l"(pol) : "l"(p.ea), "r"(p.E * PFA), "r"(p.E * 32));
  const uint32_t eru = __reduce_max_sync(~0u, ering);
  const uint32_t zr = p.force_slow;
  uint32_t rk[4];
#pragma unroll
  for (int k = 0; k < 4; k++) rk[k] = (rq ^ (k * 32)) + lds32(A_MISC);
  uint32_t nd3, mk, ln, gl = 10, gc = 0;
  auto lane_id = []() { uint32_t l; asm volatile("mov.u32 %0, %%laneid;" : "=r"(l)); return l; };
  auto slot_node = [&](uint32_t l) { return __shfl_sync(~0u, nd3, ((l >> 2) & 6) | ((l >> 1) & 1)); };
  auto lswitch = [&]() {
    const uint32_t l = lane_id();
    TA = A_TAB + (ln ? (slot_node(l) >> gl) & 1023 : 384) * (CAP * 2) + ((l >> 1) & 2);
    if (ln) mk |= 32u << (ln & 255);
    else if (atoms_incp(A_MISC + 4, l == 0) == 31) {
      proxy_fence();
      mbar_expect(BAR_U, 16384);
      tma_load(A_TAB, tmb + TM_WH, 0, BAR_U); tma_load(A_TAB + 8192, tmb + TM_WH, 64, BAR_U);
    }
    __syncwarp();
    ln >>= 8; gl += 10;
  };
  auto pswitch = [&]() {
    const uint32_t l = lane_id(), nd = (nd3 >> gc) & 1023;
    const uint32_t a = ((l & 8) ? A_WD2 + (l & 7) * 144 : A_PT + nd * 128 + ((nd & 7) << 4)) ^ (l & 16);
#pragma unroll
    for (int k = 0; k < 4; k++) ldsm4t(PB[4 * k], PB[4 * k + 1], PB[4 * k + 2], PB[4 * k + 3], a ^ (k << 5));
    OP = lds16(A_POSH + __shfl_sync(~0u, nd, l >> 2) * 8 + (l & 3) * 2) * 0x10001;
  };
  auto flush = [&](int hf, uint32_t g) {
    const uint32_t l = lane_id(), nd = (nd3 >> g) & 1023, a = A_PT + nd * 128 + (((l >> 3) ^ (nd & 7)) << 4);
    stsm4(a ^ (hf << 6), MS[4 * hf], MS[4 * hf + 1], MS[4 * hf + 2], MS[4 * hf + 3]);
    if (hf) { sts16(A_POSH + __shfl_sync(~0u, nd, l >> 2) * 8 + (l & 3) * 2, hadd(U, U >> 16)); U = 0; }
#pragma unroll
    for (int j = 4 * hf; j < 4 * hf + 4; j++) MS[j] = 0;
  };
  auto look1 = [&]() { asm volatile("ld.volatile.shared.u16 %0, [%1];" : "=r"(tn) : "r"(TA) : "memory"); asm volatile("add.u32 %0, %0, 4;" : "+r"(TA)); };
  auto look2 = [&](uint32_t tn) {
    asm volatile("ld.volatile.shared.u32 %0, [%1];" : "=r"(rn) : "r"(A_IN + tn) : "memory");
    tt = __umulhi(tn, 3728271u) * p.EPC4 + (rn >> 16); rn &= 0xFFFF;
    if (ABL & 1) tt = (tt & 0x1FFFF) + 65536;
  };
  auto issue_q = [&](uint32_t rec) {
#pragma unroll
    for (int i = 0; i < 4; i++)
      if (ABL & 2) asm volatile("{.reg .b64 a; .reg .pred p, l; setp.eq.u32 p, %2, 0xFFFF; setp.ge.u32 l, %3, 8; mad.wide.u32 a, %2, 128, %1;\n @l cp.async.cg.shared.global [%0], [a], 16, p;}"
        :: "r"(dq + i * 128), "l"((i & 1) ? qp1 : qp0), "r"(__shfl_sync(~0u, rec, 2 * i, 8)), "r"(zr) : "memory");
      else asm volatile("{.reg .b64 a; .reg .pred p; setp.eq.u32 p, %2, 0xFFFF; mad.wide.u32 a, %2, 128, %1;\n cp.async.cg.shared.global [%0], [a], 16, p;}"
        :: "r"(dq + i * 128), "l"((i & 1) ? qp1 : qp0), "r"(__shfl_sync(~0u, rec, 2 * i, 8)) : "memory");
    asm volatile("cp.async.commit_group;" ::: "memory");
    dq ^= 2048;
  };
  auto issue_e = [&](uint32_t a, uint32_t rn, uint32_t tt) {
    if (ABL & 2) asm volatile("{.reg .b64 a; .reg .pred p, l; setp.eq.u32 p, %3, 0xFFFF; setp.ge.u32 l, %5, 8; mad.wide.u32 a, %2, 32, %1;\n @l cp.async.cg.shared.global.L2::cache_hint [%0], [a], 16, p, %4;}"
      :: "r"(a), "l"(epp), "r"(tt), "r"(rn), "l"(pol), "r"(zr) : "memory");
    else asm volatile("{.reg .b64 a; .reg .pred p; setp.eq.u32 p, %3, 0xFFFF; mad.wide.u32 a, %2, 32, %1;\n cp.async.cg.shared.global.L2::cache_hint [%0], [a], 16, p, %4;}"
      :: "r"(a), "l"(epp), "r"(tt), "r"(rn), "l"(pol) : "memory");
  };
  auto act = [&](const uint32_t* y, int k) {
#pragma unroll
    for (int i = 0; i < 4; i++) { m[4 * k + i] = hsilu(y[i]); MS[2 * k + (i >> 1)] = hadd(MS[2 * k + (i >> 1)], m[4 * k + i]); }
  };
  auto cfin = [&](uint32_t d) {
    uint32_t c0_ = 0, c1_ = 0;
#pragma unroll
    for (int k = 0; k < 4; k++) { const int kk = (VAR & 32) ? k : k ^ 2; hmma(c0_, c1_, m + 4 * kk, WX[2 * kk], WX[2 * kk + 1]); }
    U = hfma(__byte_perm(c0_, c1_, 0x5410), d, U);
  };
  auto events = [&]() {
    if (mk & 1) flush(1, gc - 10);
    if (mk & 2) { flush(0, gc); gc += 10; pswitch(); }
    if (mk & 32) lswitch();
    if (mk < 16) {
      const uint32_t l = lane_id(); int cta; asm volatile("mov.u32 %0, %%ctaid.x;" : "=r"(cta));
      rec = ((slot_node(l) >> (mk < 8 ? 20 : (l & 4) ? 10 : 0)) & 1023) + cta * p.NPC;
      if (rec >= p.N || (mk < 8 && (l & 4))) rec = 0xFFFF;
      qp0 = (uint64_t)p.h + (qp0 & 127); qp1 = qp0 ^ 16;
    }
  };
  auto step = [&](uint32_t st) {
    asm volatile("cp.async.wait_group 1;" ::: "memory");
    uint32_t E[4];
    ldsm4(E, re + eru);
#pragma unroll
    for (int k = 0; k < 4; k++) ldsm4(acc + 4 * k, rk[k] + st);
    look2(tn);
    issue_q(rec);
    issue_e(re + de, rn, tt); rec = rn;
    look1();
    re = __viaddmin_u32(re, -512, rtop);
    if (ABL & 4) { U ^= (E[0] ^ acc[0] ^ acc[4] ^ acc[8] ^ acc[12]) & zr; return; }
#pragma unroll
    for (int i = 0; i < 4; i++) A1[i] = pack_f16(__uint_as_float(__byte_perm(E[i], 0, 0x1044)), bf_hi(E[i]));
    const uint32_t Sa = decode(acc[0], acc[2], acc[4], acc[6]), Sb = decode(acc[1], acc[3], acc[5], acc[7]);
    const uint32_t Dp = D;
    D = hsub(OP, __byte_perm(Sa, Sb, 0x6420));
    const __half2 d = *(const __half2*)&D, x = __hmul2(d, d), y = __hmul2(__high2half2(d), __high2half2(d));
    A2[2] = *(const uint32_t*)&x; A2[3] = *(const uint32_t*)&y;
    if (VAR & 1) yh[4] |= A1[3] & zr;
    if (VAR & 2) yh[6] |= A2[3] & zr;
    act(yh, 2); act(yh + 4, 3);
#pragma unroll
    for (int j = 0; j < 8; j++) { hmma(acc[2 * j], acc[2 * j + 1], A1, W3[2 * j], W3[2 * j + 1]); hmma(acc[2 * j], acc[2 * j + 1], A2, PB[2 * j], PB[2 * j + 1]); }
    if (VAR & 4) m[(VAR & 32) ? 0 : 8] |= acc[0] & zr;
    cfin(Dp);
    if (VAR & 8) acc[6] |= acc[14] & zr;
    if (VAR & 16) acc[7] |= acc[10] & zr;
    if (VAR & 64) acc[5] |= acc[8] & zr;
    if (VAR & 128) acc[3] |= tt & zr;
    if (VAR & 256) acc[6] |= U & zr;
    if (VAR & 512) acc[2] |= m[15] & zr;
    if (VAR & 1024) acc[4] |= acc[12] & zr;
    act(acc, 0); act(acc + 4, 1);
#pragma unroll
    for (int i = 0; i < 8; i++) yh[i] = acc[8 + i];
  };
#pragma unroll
  for (int i = 0; i < 8; i++) { m[i] = 0; yh[i] = 0; MS[i] = 0; A1[i & 3] = 0; }
  { const uint32_t sc = p.sched[wid], g0 = sc & 63, g1 = (sc >> 6) & 63, g2 = sc >> 12;
    TA = A_TAB + lds16(A_ROWS + g0 * 16 + oc * 4 + (lane & 2)) * (CAP * 2) + ((lane >> 1) & 2);
    nd3 = lds16(A_ROWS + g0 * 16 + r7 * 2) | (lds16(A_ROWS + g1 * 16 + r7 * 2) << 10) | (lds16(A_ROWS + g2 * 16 + r7 * 2) << 20);
    ln = __reduce_max_sync(~0u, lds32(A_LEN + g0 * 4) | (lds32(A_LEN + g1 * 4) << 8) | (lds32(A_LEN + g2 * 4) << 16));
    mk = 2u << max(ln & 255, 4u); ln >>= 8;
    uint32_t t3[3], ra, rb;
#pragma unroll
    for (int k = 0; k < 3; k++) { look1(); t3[k] = tn; }
    look1();
    look2(t3[0]); ra = rn; const uint32_t ta = tt;
    look2(t3[1]); rb = rn; const uint32_t tb = tt;
    look2(t3[2]);
    issue_e(re + de, ra, ta); issue_e(re + de - 512, rb, tb);
    mbar_wait(BAR_Q, 0);
    STAMP(8);
    issue_q(ra);
    pswitch();
    issue_q(rb); issue_e(re + de - 1024, rn, tt); rec = rn;
  }
  sl = 2048;
#pragma unroll 1
  do {
    if ((mk & 35) || mk < 16) events();
    sl ^= 2048; asm volatile("shr.u32 %0, %0, 1;" : "+r"(mk)); step(sl);
  } while (mk >= 4);
  sl += lds32(A_MISC); rq = rk[0] + lds32(A_MISC); dq = (dq + lds32(A_MISC)) & ~2048u;
  if (mk & 1) flush(1, gc - 10);
  STAMP(9);
  {
    int cta; asm volatile("mov.u32 %0, %%ctaid.x;" : "=r"(cta));
    const uint32_t l = lane_id(), node0 = cta * p.NPC; const int nloc = min(p.NPC, p.N - (int)node0);
    constexpr uint64_t dW = DHI | (A_TAB >> 4);
    float y1[32], y2[32];
    uint32_t H[16], po[3];
    asm volatile("cp.async.wait_group 1;" ::: "memory");
    __syncwarp();
    { const uint32_t nd = (nd3 >> ((l & 8) ? 10 : 0)) & 1023, a = A_PT + nd * 128 + (((l >> 4) ^ (nd & 7)) << 4);
#pragma unroll
      for (int k = 0; k < 4; k++) { ldsm4(acc + 4 * k, a ^ (k << 5)); ldsm4(H + 4 * k, (rq ^ (k * 32)) + (sl ^ 2048)); } }
    mbar_wait(BAR_U, 0);
    STAMP(10);
    wg_fence();
    rh64<0>(y1, acc, dW + 512); rh64<1>(y1, acc + 4, dW + 640); rh64<1>(y1, acc + 8, dW + 768); rh64<1>(y1, acc + 12, dW + 896);
    rs64<1>(y1, H, dW); rs64<1>(y1, H + 4, dW + 128); rs64<1>(y1, H + 8, dW + 256); rs64<1>(y1, H + 12, dW + 384);
    wg_commit();
    act(yh, 2); act(yh + 4, 3); cfin(D);
    sts16(A_POSH + (__shfl_sync(~0u, nd3, l >> 2) >> 20) * 8 + (l & 3) * 2, hadd(U, U >> 16));
    __syncwarp();
    if (l == 0) mbar_arrive(BAR_A);
    asm volatile("cp.async.wait_group 0;" ::: "memory");
    __syncwarp();
    wg_wait0(); fence_regs(y1);
#pragma unroll
    for (int k = 0; k < 4; k++) ldsm4(H + 4 * k, (rq ^ (k * 32)) + sl);
#pragma unroll
    for (int j = 0; j < 8; j++) acc[2 * j] = MS[j];
    wg_fence();
    rh64<0>(y2, acc, dW + 512); rh64<1>(y2, acc + 4, dW + 640); rh64<1>(y2, acc + 8, dW + 768); rh64<1>(y2, acc + 12, dW + 896);
    rs64<1>(y2, H, dW); rs64<1>(y2, H + 4, dW + 128); rs64<1>(y2, H + 8, dW + 256); rs64<1>(y2, H + 12, dW + 384);
    wg_commit();
    const float ov = y1[0] * y1[2];
    auto fin = [&](uint32_t x, float a, float b) { return badd(x, pack_bf16(silu(a), silu(b))); };
#pragma unroll
    for (int k = 0; k < 4; k += 2) {
      const uint32_t a = (rq ^ (k * 32)) + (sl ^ 2048); uint32_t x[8];
      ldsm4(x, a); ldsm4(x + 4, a ^ 32);
#pragma unroll
      for (int j = 0; j < 8; j++) x[j] = fin(x[j], y1[8 * k + 2 * j], y1[8 * k + 2 * j + 1]);
      stsm4(a, x[0], x[1], x[2], x[3]); stsm4(a ^ 32, x[4], x[5], x[6], x[7]);
    }
    { const uint32_t n0 = __shfl_sync(~0u, nd3, (l >> 2) & 6), n1 = __shfl_sync(~0u, nd3, ((l >> 2) & 6) | 1);
#pragma unroll
      for (int g = 0; g < 3; g++) po[g] = ((n0 >> (10 * g)) & 1023) | (((n1 >> (10 * g)) & 1023) << 16); }
    const uint64_t ob = (uint64_t)(p.out + (size_t)node0 * 64) + (((l & 7) ^ ((l >> 2) & 6)) << 4);
    auto put = [&](uint32_t a, uint32_t nn) {
      uint32_t v[8]; lds128(v, a); lds128(v + 4, a + 128);
#pragma unroll
      for (int i = 0; i < 2; i++)
        asm volatile("{.reg .pred p; .reg .b64 a; setp.lt.s32 p, %0, %1; mad.wide.u32 a, %0, 128, %2; @p st.global.v4.u32 [a], {%3,%4,%5,%6};}"
          :: "r"(i ? nn >> 16 : nn & 0xFFFF), "r"(nloc), "l"(ob ^ (i << 4)), "r"(v[4 * i]), "r"(v[4 * i + 1]), "r"(v[4 * i + 2]), "r"(v[4 * i + 3]) : "memory");
    };
    wg_wait0(); fence_regs(y2);
    __syncwarp();
    put(dq + (sl ^ 2048), po[0]); put(dq + 256 + (sl ^ 2048), po[1]);
    bool bad = !(fabsf(ov * y2[0] * 0.f) < 1.f);
#pragma unroll
    for (int j = 0; j < 16; j += 2) H[j] = fin(H[j], y2[2 * j], y2[2 * j + 1]);
#pragma unroll
    for (int k = 0; k < 4; k++) stsm4((rq ^ (k * 32)) + sl, H[4 * k], H[4 * k + 1], H[4 * k + 2], H[4 * k + 3]);
    __syncwarp();
    put(dq + sl, po[2]);
    const uint32_t c = __shfl_sync(~0u, atoms_incp(A_MISC + 8, l == 0), 0);
    if (c < 6) {
      mbar_wait(BAR_A, 0);
      uint32_t x[6];
#pragma unroll
      for (int k = 0; k < 6; k++) {
        const uint32_t i = c * 192 + k * 32 + l, u = lds16(A_POSH + i * 2 + i / 3 * 2);
        bad |= (u & 0x7C00) == 0x7C00;
        x[k] = pack_bf16(fmaf(__half2float(__ushort_as_half(u)), __uint_as_float(lds32(A_MISC + 12)), bf_lo(lds16(A_POSB + i * 2))), 0.f);
      }
      uint16_t* op = p.out + (size_t)p.N * 64 + (size_t)node0 * 3 + c * 192 + l;
#pragma unroll
      for (int k = 0; k < 6; k++)
        asm volatile("{.reg .pred p; setp.lt.s32 p, %0, %1; @p st.global.u16 [%2], %3;}" :: "r"(c * 192 + k * 32 + l), "r"(nloc * 3), "l"(op + k * 32), "h"((uint16_t)x[k]) : "memory");
    }
    if (__syncthreads_or(bad) && !ABL) { slow_path(p); return; }
  }
  STAMP(11);
}

}

typedef CUresult (*EncodeFn)(CUtensorMap*, CUtensorMapDataType, cuuint32_t, void*, const cuuint64_t*, const cuuint64_t*, const cuuint32_t*, const cuuint32_t*,
                             CUtensorMapInterleave, CUtensorMapSwizzle, CUtensorMapL2promotion, CUtensorMapFloatOOBfill);

extern "C" void kernel_launch(void* const* d_in, const int* in_sizes, int n_in, void* d_out, int out_size) {
  Params p; Maps maps;
  p.h = (const uint16_t*)d_in[0]; p.pos = (const uint16_t*)d_in[1]; p.ea = (const uint16_t*)d_in[2];
  p.src = (const int*)d_in[3]; p.dst = (const int*)d_in[4];
  p.we = (const uint16_t*)d_in[5]; p.wx = (const uint16_t*)d_in[6]; p.wh = (const uint16_t*)d_in[7];
  p.out = (uint16_t*)d_out;
  p.N = in_sizes[0] / 64; p.E = in_sizes[3];
  p.NPC = (p.N + G - 1) / G;
  p.EPC = ((p.E + G * 4 - 1) / (G * 4)) * 4;
  p.magic = (uint32_t)((1ull << 32) / (uint64_t)p.NPC) + 1;
  const uint32_t scheds[6][16] = {{0x2d504, 0x29783, 0x2b8c2, 0x2a38b, 0x28448, 0x1f68c, 0x185d3, 0x22747, 0x2558a, 0x2e345, 0x2f9c0, 0x2c901, 0x26646, 0x216c9, 0x1c550, 0x2048f},
    {0x2d288, 0x2840b, 0x2a6c5, 0x2e701, 0x24844, 0x297c2, 0x204cf, 0x25587, 0x1e5cc, 0x2b683, 0x2f980, 0x27489, 0x2c446, 0x1d64e, 0x2254d, 0x23614},
    {0x2fa00, 0x277c4, 0x2a585, 0x225c9, 0x1e6cf, 0x2b448, 0x24510, 0x25687, 0x2354c, 0x2d701, 0x26606, 0x1d64b, 0x2e482, 0x214cd, 0x2938a, 0x2c803},
    {0x2fa00, 0x27904, 0x29705, 0x2360b, 0x2640d, 0x2a38a, 0x1f551, 0x25647, 0x2068c, 0x2d781, 0x216c8, 0x22589, 0x2e4c2, 0x17512, 0x2b3c6, 0x2c743},
    {0x2178a, 0x2a40d, 0x1a655, 0x283cc, 0x2b5c5, 0x247c6, 0x224ce, 0x23607, 0x2e483, 0x2c2c9, 0x2f9c0, 0x2d701, 0x29504, 0x1d6c8, 0x26802, 0x25591},
    {0x2a4c9, 0x2b744, 0x2e6c2, 0x2458b, 0x29705, 0x235cc, 0x2640d, 0x2250f, 0x20787, 0x2d443, 0x2fa00, 0x2c841, 0x2738a, 0x1f648, 0x18552, 0x25686}};
  const uint32_t* sched = scheds[SCH];
  for (int i = 0; i < 16; i++) p.sched[i] = sched[i];
  p.EPC4 = p.EPC * 4;
  uint64_t al = (uint64_t)d_out;
  for (int i = 0; i < 8; i++) if (i != 1) al |= (uint64_t)d_in[i];
  p.force_slow = (al & 127) || (p.E & 3) || p.NPC > 384 || p.NPC < 2 || p.EPC > 6144;
  cudaGetSymbolAddress((void**)&p.s, g_s);
  void* fn = nullptr; cudaDriverEntryPointQueryResult qr;
  cudaGetDriverEntryPoint("cuTensorMapEncodeTiled", &fn, cudaEnableDefault, &qr);
  auto mk = [&](CUtensorMap* tm, void* base, int rows, int box) {
    const cuuint64_t dim[2] = {64, (cuuint64_t)rows}, str[1] = {128}; const cuuint32_t bx[2] = {64, (cuuint32_t)box}, es[2] = {1, 1};
    ((EncodeFn)fn)(tm, CU_TENSOR_MAP_DATA_TYPE_BFLOAT16, 2, base, dim, str, bx, es, CU_TENSOR_MAP_INTERLEAVE_NONE, CU_TENSOR_MAP_SWIZZLE_128B,
                   CU_TENSOR_MAP_L2_PROMOTION_NONE, CU_TENSOR_MAP_FLOAT_OOB_FILL_NONE);
  };
  mk(&maps.m[TM_H / 128], d_in[0], p.N, 64); mk(&maps.m[TM_WE / 128], d_in[5], 145, 64); mk(&maps.m[TM_WH / 128], p.s->wh, 128, 64);
  mk(&maps.m[TM_Q / 128], p.s->q, p.N, 64);
  mk(&maps.m[TM_W3 / 128], d_in[5], 145, 16);
  for (int k = 0; k < 2; k++) {
    const cuuint64_t dim[2] = {(cuuint64_t)G * (192 >> k), (cuuint64_t)G}, str[1] = {(cuuint64_t)G * FS}; const cuuint32_t bx[2] = {64, G}, es[2] = {1, 1};
    ((EncodeFn)fn)(&maps.m[TM_XA / 128 + k], k ? CU_TENSOR_MAP_DATA_TYPE_UINT32 : CU_TENSOR_MAP_DATA_TYPE_UINT16, 2, p.s->x, dim, str, bx, es, CU_TENSOR_MAP_INTERLEAVE_NONE,
                   CU_TENSOR_MAP_SWIZZLE_NONE, CU_TENSOR_MAP_L2_PROMOTION_NONE, CU_TENSOR_MAP_FLOAT_OOB_FILL_NONE);
  }
  cudaFuncSetAttribute(egnn_kernel, cudaFuncAttributeMaxDynamicSharedMemorySize, SMEM);
  egnn_kernel<<<G, NT, SMEM>>>(p, maps);
}
```

```cpp
#include <cuda_runtime.h>
#include <cuda_bf16.h>
#include <cuda_fp16.h>
#include <cuda.h>
#include <stdint.h>

#define SCH 3
#define PFA 6
#define PL 0
#define T3 0
#define FR 2
#define XD 0
#define WIN 6
namespace {

constexpr int G = 132;
constexpr int NT = 512;
constexpr int CAP = 48;
constexpr int FS = 384;
constexpr int BS = 1152;
constexpr uint32_t sb = 1024;

constexpr uint32_t A_RING = sb;
constexpr uint32_t A_PT = A_RING + 16 * 5120;
constexpr uint32_t A_W3 = A_PT + 49152;
constexpr uint32_t A_TAB = A_W3 + 2048;
constexpr uint32_t A_IN = A_TAB + 37888;
constexpr uint32_t A_WD = A_IN + G * FS + 512;
constexpr uint32_t A_WD2 = A_WD + 256;
constexpr uint32_t A_BAR = A_WD2 + 1024;
constexpr uint32_t A_MISC = A_BAR + 160;
constexpr uint32_t A_DH = A_MISC + 16;
constexpr uint32_t A_CNT = A_DH + 256;
constexpr uint32_t A_POSH = A_CNT + 2176;
constexpr uint32_t A_POSB = A_POSH + 3072;
constexpr uint32_t A_ROWS = A_POSB + 2304;
constexpr uint32_t A_LEN = A_ROWS + 768;
constexpr uint32_t A_END = A_LEN + 192;
constexpr uint32_t A_XC = A_TAB + 385 * CAP * 2, A_TRASH = A_XC + 144;
constexpr uint32_t A_E3 = A_IN + G / 4 * BS;
constexpr uint32_t A_WHS = A_PT - 128;
constexpr int SMEM = A_END - sb;
static_assert(SMEM <= 232448 && A_TAB % 1024 == 0 && A_IN % 1024 == 0 && A_PT % 1024 == 0 && A_WD2 % 128 == 0 && A_ROWS % 16 == 0, "smem");
constexpr int NX = 384, CH = NX * 16;
constexpr uint32_t A_QS = A_RING, A_W = A_QS + 49152, A_SA = A_IN, A_SB = A_SA + (G + 1) * 128, A_SRC = A_TAB;
__host__ __device__ constexpr uint32_t a_dst(int k) { return k < 2 ? A_W + 16384 + k * CH : A_SRC + (k + 2) * CH; }
static_assert(a_dst(1) + CH <= A_PT && a_dst(3) + CH <= A_IN && A_SB + (G + 1) * 256 <= A_WD, "staging");
constexpr uint32_t BAR_C = A_BAR, BAR_T = BAR_C + 64, BAR_W = A_BAR + 112, BAR_U = A_BAR + 120, BAR_Q = A_BAR + 128, BAR_X = A_BAR + 136, BAR_A = A_BAR + 144;

#define ABL 0
#define VAR 1056
#define HW0 4
constexpr int NREP = 8;
struct Scratch {
  uint4 q[(G * 384 + 64) * 8];
  uint4 x[G * G * 24];
  uint2 xe[G * G * 32];
  uint32_t wh[128 * 32];
  uint32_t ep[G * 32];
  uint32_t cnt[NREP * 32];
};
__device__ __align__(256) Scratch g_s;
#define STAMP(k)

struct Maps { CUtensorMap m[7]; };
constexpr int TM_H = 0, TM_WE = 128, TM_WH = 256, TM_Q = 384, TM_XA = 512, TM_XB = 640, TM_W3 = 768;
struct Params {
  const int* dst; const int* src; int E, EPC, force_slow, NPC; Scratch* s; int N; uint32_t magic;
  const uint16_t* h; const uint16_t* pos; const uint16_t* ea; const uint16_t* we; const uint16_t* wx; const uint16_t* wh; uint16_t* out;
  uint32_t EPC4, sched[16];
};

#define R32(d) "+f"(d[0]),"+f"(d[1]),"+f"(d[2]),"+f"(d[3]),"+f"(d[4]),"+f"(d[5]),"+f"(d[6]),"+f"(d[7]),"+f"(d[8]),"+f"(d[9]),"+f"(d[10]),"+f"(d[11]),"+f"(d[12]),"+f"(d[13]),"+f"(d[14]),"+f"(d[15]),"+f"(d[16]),"+f"(d[17]),"+f"(d[18]),"+f"(d[19]),"+f"(d[20]),"+f"(d[21]),"+f"(d[22]),"+f"(d[23]),"+f"(d[24]),"+f"(d[25]),"+f"(d[26]),"+f"(d[27]),"+f"(d[28]),"+f"(d[29]),"+f"(d[30]),"+f"(d[31])
#define S32 "{%0,%1,%2,%3,%4,%5,%6,%7,%8,%9,%10,%11,%12,%13,%14,%15,%16,%17,%18,%19,%20,%21,%22,%23,%24,%25,%26,%27,%28,%29,%30,%31}"
#define R16(d) "+f"(d[0]),"+f"(d[1]),"+f"(d[2]),"+f"(d[3]),"+f"(d[4]),"+f"(d[5]),"+f"(d[6]),"+f"(d[7]),"+f"(d[8]),"+f"(d[9]),"+f"(d[10]),"+f"(d[11]),"+f"(d[12]),"+f"(d[13]),"+f"(d[14]),"+f"(d[15])
#define S16 "{%0,%1,%2,%3,%4,%5,%6,%7,%8,%9,%10,%11,%12,%13,%14,%15}"
#define DI __device__ __forceinline__

constexpr uint64_t DHI = (64ull << 32) | (1ull << 62);
template<int SD> DI void ss64(float (&d)[32], uint64_t da, uint64_t db) {
  asm volatile("wgmma.mma_async.sync.aligned.m64n64k16.f32.bf16.bf16 " S32 ", %32, %33, %34, 1, 1, 0, 1;" : R32(d) : "l"(da), "l"(db), "n"(SD)); }
template<int SD> DI void rs64(float (&d)[32], const uint32_t* a, uint64_t db) {
  asm volatile("wgmma.mma_async.sync.aligned.m64n64k16.f32.bf16.bf16 " S32 ", {%32,%33,%34,%35}, %36, %37, 1, 1, 1;" : R32(d) : "r"(a[0]), "r"(a[1]), "r"(a[2]), "r"(a[3]), "l"(db), "n"(SD)); }
template<int SD> DI void rh64(float (&d)[32], const uint32_t* a, uint64_t db) {
  asm volatile("wgmma.mma_async.sync.aligned.m64n64k16.f32.f16.f16 " S32 ", {%32,%33,%34,%35}, %36, %37, 1, 1, 1;" : R32(d) : "r"(a[0]), "r"(a[1]), "r"(a[2]), "r"(a[3]), "l"(db), "n"(SD)); }
DI void wg_fence() { asm volatile("wgmma.fence.sync.aligned;" ::: "memory"); }
DI void wg_commit() { asm volatile("wgmma.commit_group.sync.aligned;" ::: "memory"); }
DI void wg_wait0() { asm volatile("wgmma.wait_group.sync.aligned 0;" ::: "memory"); }
DI void fence_regs(float (&d)[32]) { asm volatile("" : R32(d) :: "memory"); }
DI void fence_regs(float (&d)[16]) { asm volatile("" : R16(d) :: "memory"); }
DI void proxy_fence() { asm volatile("fence.proxy.async.shared::cta;" ::: "memory"); }
DI void hmma(uint32_t& d0, uint32_t& d1, const uint32_t* a, uint32_t b0, uint32_t b1) {
  asm("mma.sync.aligned.m16n8k16.row.col.f16.f16.f16.f16 {%0,%1}, {%2,%3,%4,%5}, {%6,%7}, {%0,%1};" : "+r"(d0), "+r"(d1) : "r"(a[0]), "r"(a[1]), "r"(a[2]), "r"(a[3]), "r"(b0), "r"(b1)); }
DI uint64_t pol_first() { uint64_t r; asm("createpolicy.fractional.L2::evict_first.b64 %0, 1.0;" : "=l"(r)); return r; }
DI float tanh_ap(float x) { float y; asm("tanh.approx.f32 %0, %1;" : "=f"(y) : "f"(x)); return y; }
DI float silu(float y) { return fmaf(y, tanh_ap(y), y); }
DI uint32_t pack_bf16(float lo, float hi) { uint32_t r; asm("cvt.rn.bf16x2.f32 %0, %1, %2;" : "=r"(r) : "f"(hi), "f"(lo)); return r; }
DI uint32_t pack_f16(float lo, float hi) { uint32_t r; asm("cvt.rn.f16x2.f32 %0, %1, %2;" : "=r"(r) : "f"(hi), "f"(lo)); return r; }
DI float bf_lo(uint32_t v) { return __uint_as_float(v << 16); }
DI float bf_hi(uint32_t v) { return __uint_as_float(v & 0xFFFF0000u); }
DI uint32_t b2h(uint32_t v) { return pack_f16(bf_lo(v), bf_hi(v)); }
DI uint32_t h2b(uint32_t v) { const float2 f = __half22float2(*(const __half2*)&v); return pack_bf16(f.x, f.y); }
DI uint32_t hadd(uint32_t a, uint32_t b) { uint32_t r; asm("add.rn.f16x2 %0, %1, %2;" : "=r"(r) : "r"(a), "r"(b)); return r; }
DI uint32_t hsub(uint32_t a, uint32_t b) { uint32_t r; asm("sub.rn.f16x2 %0, %1, %2;" : "=r"(r) : "r"(a), "r"(b)); return r; }
DI uint32_t hfma(uint32_t a, uint32_t b, uint32_t c) { uint32_t r; asm("fma.rn.f16x2 %0, %1, %2, %3;" : "=r"(r) : "r"(a), "r"(b), "r"(c)); return r; }
DI uint32_t hsilu(uint32_t y) { uint32_t t; asm("tanh.approx.f16x2 %0, %1;" : "=r"(t) : "r"(y)); return hfma(y, t, y); }
DI uint32_t badd(uint32_t a, uint32_t b) { uint32_t r; asm("add.rn.bf16x2 %0, %1, %2;" : "=r"(r) : "r"(a), "r"(b)); return r; }
DI uint32_t bhalf(uint32_t v) { uint32_t r; asm("mul.rn.bf16x2 %0, %1, %2;" : "=r"(r) : "r"(v), "r"(0x3F003F00u)); return r; }
DI uint32_t amax2(uint32_t mx, uint32_t v) { return __vmaxu2(mx, v & 0x7FFF7FFFu); }
DI uint32_t amax_warp(uint32_t mx) { return __reduce_max_sync(~0u, max(mx & 0xFFFF, mx >> 16)); }
DI uint32_t decode(uint32_t a, uint32_t b, uint32_t c, uint32_t d) {
  if (XD) return a ^ __funnelshift_l(b, b, 2) ^ __funnelshift_l(c, c, 4) ^ __funnelshift_l(d, d, 6);
  return a + b * 4 + c * 16 + d * 64;
}
DI void mbar_wait(uint32_t bar, uint32_t parity) {
  asm volatile("{.reg .pred p; .reg .u32 c; mov.u32 c, 0;\n"
    "LW_%=: mbarrier.try_wait.parity.shared::cta.b64 p, [%0], %1;\n"
    "@p bra.uni LD_%=;\n add.u32 c, c, 1; setp.lt.u32 p, c, 20000000;\n @p bra.uni LW_%=;\n LD_%=:}" :: "r"(bar), "r"(parity) : "memory");
}
DI void mbar_arrive(uint32_t bar) { asm volatile("mbarrier.arrive.shared::cta.b64 _, [%0];" :: "r"(bar) : "memory"); }
DI void bar_sync(int id, int n) { asm volatile("bar.sync %0, %1;" :: "r"(id), "r"(n) : "memory"); }
DI void bar_arrive(int id, int n) { asm volatile("bar.arrive %0, %1;" :: "r"(id), "r"(n) : "memory"); }
DI void sts128(uint32_t a, uint32_t x, uint32_t y, uint32_t z, uint32_t w) { asm volatile("st.shared.v4.u32 [%0], {%1,%2,%3,%4};" :: "r"(a), "r"(x), "r"(y), "r"(z), "r"(w) : "memory"); }
DI void sts64(uint32_t a, uint32_t x, uint32_t y) { asm volatile("st.shared.v2.u32 [%0], {%1,%2};" :: "r"(a), "r"(x), "r"(y) : "memory"); }
DI void sts32(uint32_t a, uint32_t x) { asm volatile("st.shared.u32 [%0], %1;" :: "r"(a), "r"(x) : "memory"); }
DI void sts16(uint32_t a, uint32_t x) { asm volatile("st.shared.u16 [%0], %1;" :: "r"(a), "h"((uint16_t)x) : "memory"); }
DI void sts32p(uint32_t a, uint32_t x, bool p) { asm volatile("{.reg .pred p; setp.ne.b32 p, %2, 0; @p st.shared.u32 [%0], %1;}" :: "r"(a), "r"(x), "r"((int)p) : "memory"); }
DI void sts16p(uint32_t a, uint32_t x, bool p) { asm volatile("{.reg .pred p; setp.ne.b32 p, %2, 0; @p st.shared.u16 [%0], %1;}" :: "r"(a), "h"((uint16_t)x), "r"((int)p) : "memory"); }
DI void lds128(uint32_t* v, uint32_t a) { asm volatile("ld.shared.v4.u32 {%0, %1, %2, %3}, [%4];" : "=r"(v[0]), "=r"(v[1]), "=r"(v[2]), "=r"(v[3]) : "r"(a) : "memory"); }
DI void lds64(uint32_t& x, uint32_t& y, uint32_t a) { asm volatile("ld.shared.v2.u32 {%0, %1}, [%2];" : "=r"(x), "=r"(y) : "r"(a) : "memory"); }
DI uint32_t lds32(uint32_t a) { uint32_t x; asm volatile("ld.shared.u32 %0, [%1];" : "=r"(x) : "r"(a) : "memory"); return x; }
DI uint32_t lds16(uint32_t a) { uint32_t x; asm volatile("ld.shared.u16 %0, [%1];" : "=r"(x) : "r"(a) : "memory"); return x; }
DI uint32_t atoms_add(uint32_t a, uint32_t v) { uint32_t r; asm volatile("atom.shared.add.u32 %0, [%1], %2;" : "=r"(r) : "r"(a), "r"(v) : "memory"); return r; }
DI uint32_t atoms_incp(uint32_t a, bool p) { uint32_t r = 0; asm volatile("{.reg .pred p; setp.ne.b32 p, %2, 0; @p atom.shared.add.u32 %0, [%1], 1;}" : "+r"(r) : "r"(a), "r"((int)p) : "memory"); return r; }
DI uint32_t ldg_poll(const void* a) { uint32_t x; asm volatile("ld.relaxed.gpu.global.u32 %0, [%1];" : "=r"(x) : "l"(a) : "memory"); return x; }
DI uint2 ldg_poll2(const void* a) { uint2 x; asm volatile("ld.relaxed.gpu.global.v2.u32 {%0, %1}, [%2];" : "=r"(x.x), "=r"(x.y) : "l"(a) : "memory"); return x; }
DI void bulk_load(uint32_t dst, const void* src, uint32_t bytes, uint32_t bar) {
  asm volatile("cp.async.bulk.shared::cluster.global.mbarrier::complete_tx::bytes.L2::cache_hint [%0], [%1], %2, [%3], %4;" :: "r"(dst), "l"(src), "r"(bytes), "r"(bar), "l"(pol_first()) : "memory"); }
DI void mbar_expect(uint32_t bar, uint32_t bytes) { asm volatile("mbarrier.arrive.expect_tx.shared::cta.b64 _, [%0], %1;" :: "r"(bar), "r"(bytes) : "memory"); }
DI void mbar_init(uint32_t bar, int n) { asm volatile("mbarrier.init.shared::cta.b64 [%0], %1;" :: "r"(bar), "r"(n) : "memory"); }
DI void tma_load(uint32_t dst, uint64_t tm, int row, uint32_t bar) {
  asm volatile("cp.async.bulk.tensor.2d.shared::cluster.global.mbarrier::complete_tx::bytes.L2::cache_hint [%0], [%1, {%3, %4}], [%2], %5;" :: "r"(dst), "l"(tm), "r"(bar), "r"(0), "r"(row), "l"(pol_first()) : "memory"); }
DI void tma_store(uint64_t tm, int col, int row, uint32_t src) {
  asm volatile("cp.async.bulk.tensor.2d.global.shared::cta.bulk_group [%0, {%2, %3}], [%1];" :: "l"(tm), "r"(src), "r"(col), "r"(row) : "memory"); }
DI void bulk_commit() { asm volatile("cp.async.bulk.commit_group;" ::: "memory"); }
DI void stsm4(uint32_t a, uint32_t x, uint32_t y, uint32_t z, uint32_t w) { asm volatile("stmatrix.sync.aligned.m8n8.x4.shared.b16 [%0], {%1,%2,%3,%4};" :: "r"(a), "r"(x), "r"(y), "r"(z), "r"(w) : "memory"); }
DI void ldsm4(uint32_t* v, uint32_t a) { asm volatile("ldmatrix.sync.aligned.m8n8.x4.shared.b16 {%0,%1,%2,%3}, [%4];" : "=r"(v[0]), "=r"(v[1]), "=r"(v[2]), "=r"(v[3]) : "r"(a) : "memory"); }
DI void ldsm4t(uint32_t& x, uint32_t& y, uint32_t& z, uint32_t& w, uint32_t a) { asm volatile("ldmatrix.sync.aligned.m8n8.x4.trans.shared.b16 {%0,%1,%2,%3}, [%4];" : "=r"(x), "=r"(y), "=r"(z), "=r"(w) : "r"(a) : "memory"); }

__device__ __noinline__ void slow_path(const Params& p) {
  const int lane = threadIdx.x & 31, wid = threadIdx.x >> 5;
  const uint32_t ab = sb + wid * (24 * 528);
  const uint32_t* we = (const uint32_t*)p.we;
  const int nend = min(p.N, (blockIdx.x + 1) * p.NPC);
  auto rowmul = [&](uint32_t hv, const uint32_t* w, float& y0, float& y1) {
#pragma unroll 4
    for (int k = 0; k < 32; k++) {
      const uint32_t hk = __shfl_sync(~0u, hv, k), wa = __ldg(w + 2 * k * 32 + lane), wb = __ldg(w + (2 * k + 1) * 32 + lane);
      y0 = fmaf(bf_lo(hk), bf_lo(wa), fmaf(bf_hi(hk), bf_lo(wb), y0)); y1 = fmaf(bf_lo(hk), bf_hi(wa), fmaf(bf_hi(hk), bf_hi(wb), y1));
    }
  };
  auto act = [](float x) { return x / (1.f + __expf(-x)); };
  auto hrow = [&](int n) { return __ldg(p.h + (size_t)n * 64 + 2 * lane) | ((uint32_t)__ldg(p.h + (size_t)n * 64 + 2 * lane + 1) << 16); };
  const uint32_t wdv = __ldg(we + 128 * 32 + lane), wxv = __ldg((const uint32_t*)p.wx + lane);
  for (int nb = blockIdx.x * p.NPC + wid * 24; nb < nend; nb += 384) {
    const int cnt = min(24, nend - nb);
    for (int n = 0; n < cnt; n++) {
      float y0 = 0.f, y1 = 0.f; rowmul(hrow(nb + n), we, y0, y1);
      sts64(ab + n * 528 + lane * 8, 0, 0); sts64(ab + n * 528 + 256 + lane * 8, __float_as_uint(y0), __float_as_uint(y1));
      if (lane < 4) sts32(ab + n * 528 + 512 + lane * 4, 0);
    }
    __syncwarp();
    for (int base = 0; base < p.E; base += 32) {
      const uint32_t dl = base + lane < p.E ? (uint32_t)(__ldg(p.dst + base + lane) - nb) : 0xFFFFFFFFu;
      uint32_t mk = __ballot_sync(~0u, dl < (uint32_t)cnt);
      while (mk) {
        const int l = __ffs(mk) - 1; mk &= mk - 1;
        const int e = base + l, n = __shfl_sync(~0u, dl, l), s = __ldg(p.src + e);
        const uint32_t a = ab + n * 528;
        float df = 0.f;
        if (lane < 3) df = bf_lo(pack_bf16(bf_lo(__ldg(p.pos + (size_t)(nb + n) * 3 + lane)) - bf_lo(__ldg(p.pos + (size_t)s * 3 + lane)), 0.f));
        float d2 = df * df; d2 += __shfl_xor_sync(~0u, d2, 1); d2 += __shfl_xor_sync(~0u, d2, 2); d2 = __shfl_sync(~0u, d2, 0);
        uint32_t x0, x1; lds64(x0, x1, a + 256 + lane * 8);
        float y0 = fmaf(d2, bf_lo(wdv), __uint_as_float(x0)), y1 = fmaf(d2, bf_hi(wdv), __uint_as_float(x1));
        rowmul(hrow(s), we + 64 * 32, y0, y1);
        for (int k = 0; k < 16; k++) { const float ev = bf_lo(__ldg(p.ea + (size_t)e * 16 + k)); const uint32_t w = __ldg(we + (129 + k) * 32 + lane); y0 = fmaf(ev, bf_lo(w), y0); y1 = fmaf(ev, bf_hi(w), y1); }
        y0 = act(y0); y1 = act(y1);
        float c = y0 * bf_lo(wxv) + y1 * bf_hi(wxv);
#pragma unroll
        for (int o = 16; o; o >>= 1) c += __shfl_xor_sync(~0u, c, o);
        lds64(x0, x1, a + lane * 8);
        sts64(a + lane * 8, __float_as_uint(__uint_as_float(x0) + y0), __float_as_uint(__uint_as_float(x1) + y1));
        if (lane < 3) sts32(a + 512 + lane * 4, __float_as_uint(fmaf(c, df, __uint_as_float(lds32(a + 512 + lane * 4)))));
      }
    }
    __syncwarp();
    for (int n = 0; n < cnt; n++) {
      const uint32_t hv = hrow(nb + n); uint32_t x0, x1; lds64(x0, x1, ab + n * 528 + lane * 8);
      float y0 = 0.f, y1 = 0.f; rowmul(hv, (const uint32_t*)p.wh, y0, y1); rowmul(pack_bf16(__uint_as_float(x0), __uint_as_float(x1)), (const uint32_t*)p.wh + 64 * 32, y0, y1);
      const uint32_t o = badd(hv, pack_bf16(act(y0), act(y1)));
      p.out[(size_t)(nb + n) * 64 + 2 * lane] = (uint16_t)o; p.out[(size_t)(nb + n) * 64 + 2 * lane + 1] = (uint16_t)(o >> 16);
      if (lane < 3) p.out[(size_t)p.N * 64 + (size_t)(nb + n) * 3 + lane] = (uint16_t)pack_bf16(bf_lo(__ldg(p.pos + (size_t)(nb + n) * 3 + lane)) + __uint_as_float(lds32(ab + n * 528 + 512 + lane * 4)), 0.f);
    }
    __syncwarp();
  }
}

__global__ void __launch_bounds__(NT, 1) egnn_kernel(const __grid_constant__ Params p, const __grid_constant__ Maps maps) {
  extern __shared__ __align__(1024) unsigned char smraw[];
  const int tid = threadIdx.x, cta = blockIdx.x;
  const int e0 = cta * p.EPC, nb = max(0, min(p.EPC, p.E - e0)) * 4;
  STAMP(0);
  auto load_idx = [&](int c) {
    const int o = (c & 3) * CH, n = max(0, min(CH, nb - o));
    mbar_expect(BAR_C + c * 8, n);
    if (n) bulk_load(c < 4 ? a_dst(c) : A_SRC + o, (const char*)((c < 4 ? p.dst : p.src) + e0) + o, n, BAR_C + c * 8);
  };
  if (tid == 480 && !p.force_slow) {
#pragma unroll
    for (int c = 0; c < 4; c++) mbar_init(BAR_C + c * 8, 1);
    asm volatile("fence.mbarrier_init.release.cluster;" ::: "memory");
#pragma unroll
    for (int c = 0; c < 4; c++) load_idx(c);
  }
  if ((uint32_t)__cvta_generic_to_shared(smraw) != sb) return;
  if (p.force_slow) { slow_path(p); return; }
  uint32_t ep = ldg_poll(p.s->ep + cta * 32), tgb;
  const uint64_t tmb = (uint64_t)&maps;
  const int lane = tid & 31, wid = __shfl_sync(~0u, tid >> 5, 0), g8 = lane >> 2, q = lane & 3;
  uint32_t whx = 0;
  if (wid < 12) {
    if (tid < (A_CNT - A_MISC) / 16) sts128(A_MISC + tid * 16, 0, tid == 0 ? 16 : 0, 0, 0);
    const uint32_t acnt = A_CNT + ((tid + cta * p.NPC) & 511) * 4;
    sts32(acnt, A_TAB + tid * (CAP * 2));
    if (tid < 32) sts32(A_CNT + 2048 + tid * 4, A_TRASH);
    ep++; tgb = ep << 31;
    const uint32_t tga = (ep & 63) * 0x04000400u, tgh = tga & 0xFFFF0000u;
    {
      const uint32_t x = tga + (512 + (tid & 7) * 4) * 0x10001u;
#pragma unroll
      for (int k = 0; k < 3; k++) if (k < 2 || tid < (G + 1) * 8 - 2 * NX) {
        const uint32_t i = tid + k * NX, hw = ((i >> 3) & 31) - (i & 7) * 4;
        sts128(A_SA + i * 16, x, x + 0x10001u, x + 0x20002u, x + 0x30003u);
        sts32p(A_SA + i * 16 + hw * 4, tgh + (i & 7) * 16 + hw * 4 + 4, hw < 4);
      }
#pragma unroll
      for (int k = 0; k < 6; k++) if (k < 5 || tid < G * 16 - 5 * NX) sts128(A_SB + (tid + k * NX) * 16, tgb, tgb, tgb, tgb);
    }
    bar_sync(7, NT);
    STAMP(23);
  } else {
    if (wid == 15) asm volatile("ld.global.nc.u32 %0, [%1];" : "=r"(whx) : "l"((const uint32_t*)p.wh + (cta & 127) * 32 + lane));
    if (tid == 480 || tid == 448) {
#pragma unroll
      for (int c = 0; c < 10; c++) if (tid == 480 || c < 5) mbar_init(BAR_C + (tid == 480 ? 32 : 112) + c * 8, tid == 448 && c == 4 ? 16 : 1);
      asm volatile("fence.mbarrier_init.release.cluster;" ::: "memory");
    }
    if (tid - 416 < 7u) asm volatile("prefetch.tensormap [%0];" :: "l"(tmb + (tid - 416) * 128));
    __syncwarp();
    if (wid == 15) bar_arrive(7, NT); else bar_sync(7, NT);
    if (tid == 480) {
#pragma unroll 1
      for (int c = 4; c < 14; c++) {
        if (c >= WIN) mbar_wait(BAR_C + (c < 8 ? c - WIN : HW0) * 8, 0);
        if (c < 8) load_idx(c); else { mbar_expect(BAR_C + c * 8, 8192); tma_load(A_PT + (c - 8) * 8192, tmb + TM_H, cta * p.NPC + (c - 8) * 64, BAR_C + c * 8); }
      }
    }
    if (tid == 448) {
      mbar_expect(BAR_W, 2 * 8192 + 2048 + 256);
      tma_load(A_W, tmb + TM_WE, 64, BAR_W); tma_load(A_W + 8192, tmb + TM_WE, 0, BAR_W); tma_load(A_W3, tmb + TM_W3, 129, BAR_W);
      bulk_load(A_WD, p.we + 128 * 64, 128, BAR_W); bulk_load(A_WD + 128, p.wx, 128, BAR_W);
    }
    __syncwarp();
  }

  const int w = wid & 3;
  const uint32_t frag = (w * 16 + (lane & 15)) * 128 + (((lane >> 4) ^ (lane & 7)) << 4), pa = A_POSH + (w * 16 + g8) * 8 + q * 2;
  float a0[32], a1[32];
  float mx = 0.f;
  auto mma = [&](float (&acc)[32], int b, int blk) {
    const uint64_t da = DHI | ((A_PT + blk * 8192) >> 4), db = DHI | ((A_W + b * 8192) >> 4);
    wg_fence();
    ss64<0>(acc, da, db); ss64<1>(acc, da + 2, db + 128); ss64<1>(acc, da + 4, db + 256); ss64<1>(acc, da + 6, db + 384);
    wg_commit();
  };
  auto epi = [&](float (&acc)[32], int b, int blk) {
    uint32_t o[16];
#pragma unroll
    for (int j = 0; j < 16; j++) o[j] = pack_f16(acc[2 * j], acc[2 * j + 1]);
    if (b) {
#pragma unroll
      for (int j = 0; j < 32; j++) mx = fmaxf(mx, fabsf(acc[j]));
    } else {
#pragma unroll
      for (int r = 0; r < 2; r++) {
        const uint32_t T = __byte_perm(lds16(pa + blk * 512 + r * 64), 0, 0x4140);
#pragma unroll
        for (int j = 0; j < 4; j++) o[2 * j + r] &= 0xFFFCFFFCu;
        const uint32_t S = decode(o[r], o[2 + r], o[4 + r], o[6 + r]);
        const uint32_t X = (T - S) & 255, Y = XD ? S ^ T : X | ((T - ((S + X) & 0xFFFF0000u)) & 0x00FF0000u);
#pragma unroll
        for (int j = 0; j < 4; j++) o[2 * j + r] |= (Y >> (2 * j)) & 0x00030003u;
      }
    }
    const uint32_t a = (b ? A_PT : A_QS) + blk * 8192 + frag;
#pragma unroll
    for (int j = 0; j < 4; j++) stsm4(a ^ (j << 5), o[4 * j], o[4 * j + 1], o[4 * j + 2], o[4 * j + 3]);
  };
  uint32_t W3[16], PB[16], WX[8];
  auto frags = [&]() {
#pragma unroll
    for (int k = 0; k < 4; k++) ldsm4t(W3[4 * k], W3[4 * k + 1], W3[4 * k + 2], W3[4 * k + 3], A_W3 + (lane & 15) * 128 + ((((lane >> 4) + 2 * k) ^ (lane & 7)) << 4));
#pragma unroll
    for (int j = 0; j < 8; j++) WX[j] = lds32(A_WD + 128 + j * 16 + q * 4);
  };
  auto p_check = [&](int blk) {
    const uint32_t pm = __reduce_max_sync(~0u, __float_as_uint(mx));
    if (pm > 0x46000000u || (pm < 0x3A800000u && blk * 64 + (w + 1) * 16 <= min(p.NPC, p.N - cta * p.NPC))) sts32(A_MISC, 1);
  };
  if (wid >= 12) {
    const int node0 = cta * p.NPC, nloc = max(0, min(p.NPC, p.N - node0));
    if (w == 3) {
      const uint32_t mh = amax_warp(whx & 0x7FFF7FFFu);
      sts32(A_WHS + lane * 4, cta < 64 ? bhalf(whx) : mh && mh < 0x3B00 ? ~0u : b2h(bhalf(whx)));
      __syncwarp();
      if (lane == 0 && cta < 128) { proxy_fence(); asm volatile("cp.async.bulk.global.shared::cta.bulk_group [%0], [%1], 128;" :: "l"(p.s->wh + cta * 32), "r"(A_WHS) : "memory"); }
      __syncwarp();
      ep++;
    }
    else {
      const int t = tid - 384;
      uint32_t ps[12], mp = 0;
#pragma unroll
      for (int k = 0; k < 4; k++) {
        ps[3 * k] = ps[3 * k + 1] = ps[3 * k + 2] = 0;
        asm volatile("{.reg .pred p; setp.lt.s32 p, %4, %5;\n @p ld.global.nc.u16 %0, [%3];\n @p ld.global.nc.u16 %1, [%3+2];\n @p ld.global.nc.u16 %2, [%3+4];}"
          : "+r"(ps[3 * k]), "+r"(ps[3 * k + 1]), "+r"(ps[3 * k + 2]) : "l"(p.pos + (size_t)(node0 + t + 96 * k) * 3), "r"(t + 96 * k), "r"(p.N - node0));
      }
      mbar_wait(BAR_W, 0);
#pragma unroll
      for (int k = 0; k < 11; k++) if (k < 10 || w < 2) { uint32_t v[4]; const uint32_t a = A_W + (t + k * 96) * 16; lds128(v, a); sts128(a, bhalf(v[0]), bhalf(v[1]), bhalf(v[2]), bhalf(v[3])); }
      const uint32_t wd = lds32(A_WD + lane * 4), md = amax_warp(wd & 0x7FFF7FFFu);
      bool bad = md - 0x3B00 > 0x680;
      if (w < 2) {
        uint32_t mw = 0;
#pragma unroll
        for (int k = 0; k < 2; k++) { uint32_t v[4]; const uint32_t a = A_W3 + (t + k * 64) * 16; lds128(v, a);
          sts128(a, b2h(bhalf(v[0])), b2h(bhalf(v[1])), b2h(bhalf(v[2])), b2h(bhalf(v[3]))); mw = amax2(amax2(amax2(amax2(mw, v[0]), v[1]), v[2]), v[3]); }
        bad |= amax_warp(mw) - 0x3B00 > 0x680;
      } else {
#pragma unroll
        for (int r = 0; r < 8; r++) sts32(A_WD2 + r * 128 + ((lane * 4) ^ (r << 4)), (r & 1) ? 0 : r == 6 ? 0xF753F753u : b2h(bhalf(wd)));
        const uint32_t x = lds32(A_WD + 128 + lane * 4), ex = min(max(amax_warp(x & 0x7FFF7FFFu) >> 7, 20u), 230u);
        const float sc = __uint_as_float((252 - ex) << 23);
        sts32(A_WD + 128 + lane * 4, pack_f16(bf_lo(x) * sc, bf_hi(x) * sc)); sts32(A_MISC + 12, (ex + 2) << 23);
      }
#pragma unroll
      for (int k = 0; k < 4; k++) {
        const int n = t + 96 * k;
        sts64(A_POSH + n * 8, pack_f16(bf_lo(ps[3 * k]), bf_lo(ps[3 * k + 1])), pack_f16(bf_lo(ps[3 * k + 2]), 1.f));
        sts16(A_POSB + n * 6, ps[3 * k]); sts16(A_POSB + n * 6 + 2, ps[3 * k + 1]); sts16(A_POSB + n * 6 + 4, ps[3 * k + 2]);
        mp = amax2(amax2(mp, ps[3 * k] | (ps[3 * k + 1] << 16)), ps[3 * k + 2]);
      }
      mp = amax_warp(mp);
      if (bad || !(bf_lo(mp) * bf_lo(mp) * bf_lo(md) < 6000.f) || (mp < 0x3B80 && (w + 1) * 32 <= nloc)) sts32(A_MISC, 1);
      proxy_fence();
      if (w == 0) STAMP(16);
      bar_arrive(3, NX + 96);
      ep++;
    }
    bar_sync(6, 128);
#pragma unroll 1
    for (int blk = T3; blk < 6; blk = max(blk + 1, 4)) {
      mbar_wait(BAR_T + blk * 8, 0);
      if (w == 0 && blk == 5) STAMP(17);
      mma(a0, 0, blk); mma(a1, 1, blk);
      asm volatile("wgmma.wait_group.sync.aligned 1;" ::: "memory"); fence_regs(a0);
      epi(a0, 0, blk);
      wg_wait0(); fence_regs(a1);
      bar_sync(6, 128);
      if (w == 3 && blk == 5) {
        bar_sync(8, NX + 32);
        if (lane == 0) {
          proxy_fence();
#pragma unroll 1
          for (int b = 0; b * 64 < nloc; b++) tma_store(tmb + TM_Q, 0, node0 + b * 64, A_QS + b * 8192);
          STAMP(18);
        }
        __syncwarp();
      }
      epi(a1, 1, blk);
    }
    p_check(T3);
    frags();
    tgb = ep << 31;
  } else {
    const uint32_t acnt = A_CNT + ((tid + cta * p.NPC) & 511) * 4, tga = (ep & 63) * 0x04000400u, tgh = tga & 0xFFFF0000u;
    tgb = ep << 31;
    uint32_t d[16], oo[16], xx[16], lc[16], mxx = 0;
#pragma unroll
    for (int c = 0; c < 4; c++) {
      mbar_wait(BAR_C + c * 8, 0);
      if (c == 3) STAMP(1);
      lds128(d + 4 * c, a_dst(c) + tid * 16);
#pragma unroll
      for (int k = 4 * c; k < 4 * c + 4; k++) {
        if (tid * 16 + c * CH >= nb) d[k] = G * p.NPC;
        const uint32_t j = __umulhi(d[k], p.magic);
        xx[k] = atoms_add(A_SA + (j * 128 | ((j * 4) & 0x7C)), 258);
        oo[k] = j * 128;
      }
    }
#pragma unroll
    for (int k = 0; k < 16; k++) { oo[k] |= xx[k] & 0x7E; mxx = max(mxx, xx[k]); }
    if (mxx > tgh + 15900) {
#pragma unroll
      for (int k = 0; k < 16; k++) if (xx[k] > tgh + 15900) oo[k] = G * 128 + 64 + lane * 2;
    }
#pragma unroll
    for (int k = 0; k < 16; k++) sts16(A_SA + oo[k], (d[k] & 511) | tga);
    if (wid == 0) { bar_sync(1, NX); if (lane == 0) { proxy_fence(); tma_store(tmb + TM_XA, cta * 192, 0, A_SA); bulk_commit(); } __syncwarp(); } else bar_arrive(1, NX);
    STAMP(2);
    const uint32_t eb = tgb + ((tid * 4 + (cta & 3) * p.EPC) << 16);
#pragma unroll
    for (int c = 0; c < 4; c++) {
      mbar_wait(BAR_C + 32 + c * 8, 0);
      if (wid == 0 && c == 3) STAMP(21);
      lds128(lc + 4 * c, A_SRC + c * CH + tid * 16);
#pragma unroll
      for (int k = 4 * c; k < 4 * c + 4; k++) { lc[k] += eb + ((c * NX * 4 + (k & 3)) << 16); sts32(A_SB + oo[k] * 2, lc[k]); }
    }
    bar_sync(2, NX);
    if (tid == 0) { proxy_fence(); tma_store(tmb + TM_XB, cta * 96 + 32, 0, A_SB); bulk_commit(); p.s->ep[cta * 32] = ep; }
    __syncwarp();
    STAMP(3);
    if (mxx > tgh + 15900) {
#pragma unroll
      for (int k = 0; k < 16; k++) {
        const uint32_t j = __umulhi(d[k], p.magic), r = (xx[k] - tgh) / 258 - 62;
        if (r < 31 && j < G)
          asm volatile("st.relaxed.gpu.global.v2.u32 [%0], {%1, %2};" :: "l"(p.s->xe + (j * G + cta) * 32 + r), "r"(lc[k]), "r"((d[k] & 511) | (ep << 9)) : "memory");
      }
    }
    __syncwarp();
    constexpr int JS = 12; const int j0 = wid;
#pragma unroll
    for (int k = 0; k < 7; k++) if (k < 6 || tid < 385 * CAP / 8 + 9 - 6 * NX) sts128(A_TAB + (tid + k * NX) * 16, 0, 0, 0, 0);
    bar_sync(3, NX + 96);
    STAMP(12);
    const char* xin = (const char*)(p.s->x + cta * G * 24);
    uint32_t pk[11];
    const uint32_t rot = (lane + cta) & 31;
    auto poll_a = [&]() {
#pragma unroll
      for (int k = 0; k < 11; k++) pk[k] = ldg_poll(xin + (j0 + JS * k) * FS + rot * 4);
    };
    uint32_t xs = ~0u; uint2 xv;
    const uint32_t t0 = (wid >> 2) * BS + 128 + w * 256 + rot * 8, tx = lane ? tga : tgh;
    const uint32_t h1 = (cta & 31) * 4 + 4 + 62 * 258;
    int spin = 0;
    auto copy_b = [&]() {
      const uint32_t o = (j0 + JS * (lane >> 4)) * FS + 128 + (lane & 15) * 16, a = A_IN + ((wid >> 2) + 3 * (lane >> 4)) * BS + 128 + w * 256 + (lane & 15) * 16;
#pragma unroll
      for (int k = 0; k < 6; k++) if (k < 5 || lane < 16)
        asm volatile("cp.async.cg.shared.global.L2::cache_hint [%0], [%1], 16, %2;" :: "r"(a + k * 6 * BS), "l"(xin + o + k * 2 * JS * FS), "l"(pol_first()) : "memory");
    };
    {
      const int blk = (wid >> 2) + !T3;
      mbar_wait(BAR_T + blk * 8, 0);
      if (wid == 8) STAMP(22);
      mma(a0, 0, blk); if (!PL) mma(a1, 1, blk);
      asm volatile("wgmma.wait_group.sync.aligned %0;" :: "n"(!PL) : "memory"); fence_regs(a0);
      epi(a0, 0, blk);
      bar_arrive(8, NX + 32);
      poll_a();
      if (PL) mma(a1, 1, blk);
      wg_wait0(); fence_regs(a1);
      bar_sync(13 + (wid >> 2), 128);
      epi(a1, 1, blk);
      p_check(blk);
      if (FR == 0) frags();
      if (wid == 8) STAMP(24);
    }
    {
      {
        for (;;) {
          uint32_t mh = 0, bad = 0;
#pragma unroll
          for (int k = 0; k < 11; k++) { pk[k] ^= tx; mh = max(mh, pk[k]); bad |= pk[k]; }
          if (!__any_sync(~0u, bad & (lane ? 0xFC00FC00u : 0xFC000000u))) {
            if (__shfl_sync(~0u, mh, 0) > h1) {
              uint32_t base = 0;
#pragma unroll
              for (int k = 0; k < 11; k++) {
                const uint32_t c = (max(__shfl_sync(~0u, pk[k], 0), h1) - h1) / 258;
                if (lane - base < c) xs = (j0 + JS * k) * 32 + lane - base;
                base += c;
              }
              if (base > 31) { sts32(A_MISC, 1); xs = ~0u; }
              if (xs != ~0u) xv = ldg_poll2(p.s->xe + cta * G * 32 + xs);
              __syncwarp();
            }
            break;
          }
          if (++spin > 2000000) __trap();
          poll_a();
        }
        STAMP(14); if (wid == 8) STAMP(25);
        uint32_t r0[11], r1[11];
#pragma unroll
        for (int k = 0; k < 11; k++) {
          if (lane == 0) pk[k] = (512 + rot) * 0x10001u;
          r0[k] = atoms_add(A_CNT + (pk[k] & 0xFFFF) * 4, 2);
          r1[k] = atoms_add(A_CNT + (pk[k] >> 16) * 4, 2);
        }
#pragma unroll
        for (int k = 0; k < 11; k++) { sts16(min(r0[k], A_IN - 2), t0 + 3 * k * BS); sts16(min(r1[k], A_IN - 2), t0 + 3 * k * BS + 4); }
        if (wid == 8) STAMP(26);
      }
    }
    if (tid == 0) { asm volatile("cp.async.bulk.wait_group.read 0;" ::: "memory"); mbar_arrive(BAR_X); }
    __syncwarp();
    mbar_wait(BAR_X, 0);
    copy_b();
    STAMP(4);
    if (xs != ~0u) {
      for (int i = 0; (((xv.x ^ tgb) >> 31) | ((xv.y >> 9) ^ (ep & 0x7FFFFF))) && i < 2000000; i++) xv = ldg_poll2(p.s->xe + cta * G * 32 + xs);
      const uint32_t n = atoms_add(A_XC + (xs >> 7) * 4, 4), t = (xs >> 7) * BS + 4 + min(n, 120u);
      if (n > 120) sts32(A_MISC, 1);
      sts16(min(atoms_add(A_CNT + (xv.y & 511) * 4, 2), A_IN - 2), t);
      sts32(A_IN + t, xv.x);
    }
    __syncwarp();
    if (FR == 1) frags();
    bar_sync(4, NX);
    STAMP(5);
    {
      const uint32_t dg = (lds32(acnt) - (A_TAB + tid * (CAP * 2))) >> 1;
      const uint32_t dr = atoms_add(A_DH + min(dg, 63u) * 4, 1);
      bar_sync(5, NX);
      uint32_t hb, ha; lds64(hb, ha, A_DH + (62 - 2 * lane) * 4);
      uint32_t inc = ha + hb;
#pragma unroll
      for (int o = 1; o < 32; o <<= 1) { const uint32_t y = __shfl_up_sync(~0u, inc, o); if (lane >= o) inc += y; }
      const uint32_t idx = 63 - min(dg, 63u);
      const uint32_t e2 = __shfl_sync(~0u, (inc - hb) | ((inc - hb - ha) << 16), idx >> 1);
      const uint32_t pos = ((idx & 1) ? (e2 & 0xFFFF) : (e2 >> 16)) + dr;
      sts16(A_ROWS + pos * 2, tid);
      if (!(pos & 7)) sts32(A_LEN + (pos >> 1), max(1u, (dg + 1) >> 1));
      if (dg > CAP) sts32(A_MISC, 1);
    }
    STAMP(6);
    if (tid == 0) sts32(A_IN, 0xFFFF);
    for (;;) {
      asm volatile("cp.async.wait_all;" ::: "memory");
      __syncwarp();
      uint32_t bad = 0;
#pragma unroll
      for (int k = 0; k < 11; k++) { uint32_t x, y; lds64(x, y, A_IN + t0 + 3 * k * BS); bad |= (x ^ tgb) | (y ^ tgb); }
      if (!__any_sync(~0u, bad >> 31) || ++spin > 2000000) break;
      copy_b();
    }
    if (FR == 2) frags();
    STAMP(7);
  }
  if (wid == 15) {
    bar_arrive(11, NT);
    if (lane == 0) { bulk_commit(); asm volatile("cp.async.bulk.wait_group 0;" ::: "memory"); }
    __syncwarp();
    if (lane < NREP) asm volatile("red.relaxed.gpu.global.add.u32 [%0], 1;" :: "l"(p.s->cnt + lane * 32) : "memory");
    if (lane == 0) {
      STAMP(19);
      const uint32_t nbe = (p.E / G) & ~15u;
#pragma unroll 1
      for (int i = 0; i < PFA; i++)
        if (nbe) asm volatile("cp.async.bulk.prefetch.L2.global [%0], %1;" :: "l"((const char*)p.ea + (size_t)(i * G + cta) * nbe), "r"(nbe) : "memory");
      uint32_t c; int spin = 0;
      do asm volatile("ld.acquire.gpu.global.u32 %0, [%1];" : "=r"(c) : "l"(p.s->cnt + (cta % NREP) * 32) : "memory"); while ((int)(c - ep * G) < 0 && ++spin < 20000000);
      mbar_arrive(BAR_Q);
      STAMP(20);
    }
    __syncwarp();
  }
  uint32_t A2[4];
  const uint32_t ring = 4096 + wid * 4096, ering = (wid < 8 ? 69632 : A_E3 - 8 * 1536) + wid * 1536;
  const int oc = lane >> 3;
  const int r7 = lane & 7, ro = r7 >> 1, ri = 2 * (oc & 1) + (r7 & 1);
  uint64_t qp0 = (uint64_t)p.s->q + ((r7 ^ (2 * oc)) << 4), qp1 = qp0 ^ 16, epp = (uint64_t)p.ea + (((lane ^ oc) & 1) << 4) - (tgb >> 11);
  uint32_t dq = ring + oc * 512 + r7 * 16, de = ering + ((lane * 16) ^ ((oc >> 1) * 64));
  uint32_t rq = ring + (4 * ro + ri) * 128 + (((oc >> 1) ^ r7) << 4), re = ering + ro * 128 + ((ri ^ (2 * (ro >> 1))) << 5) + ((((oc >> 1) ^ ro) & 1) << 4);
  A2[0] = (g8 >> 1) == q ? ((g8 & 1) ? 0x3C000000u : 0x3C00u) : 0;
  A2[0] += lds32(A_MISC + 8); A2[1] = A2[0] + lds32(A_MISC + 8);
  asm volatile("" : "+l"(qp0), "+l"(qp1), "+l"(epp), "+r"(dq), "+r"(de), "+r"(rq), "+r"(re));
  bar_sync(wid < 15 ? 11 : 12, wid < 15 ? NT : 64);
  if (wid == 14) bar_arrive(12, 64);
  STAMP(13);
  if (__any_sync(~0u, lds32(A_MISC))) { sts32(A_MISC + 12, dq ^ de ^ rq ^ re ^ (uint32_t)qp0 ^ (uint32_t)qp1 ^ (uint32_t)(epp ^ (epp >> 32)) ^ A2[1]); __syncthreads(); slow_path(p); return; }

  uint32_t MS[8], acc[16], m[16], yh[8], A1[4], OP, TA, D = 0, U = 0, tt, tn, rec, rn, sl;
  re += lds32(A_MISC) + 1024 - ering; de += lds32(A_MISC) + 1024 - re; const uint32_t rtop = re + lds32(A_MISC);
  uint64_t pol;
  asm("createpolicy.range.global.L2::evict_normal.L2::evict_first.b64 %0, [%1], %2, %3;" : "=l"(pol) : "l"(p.ea), "r"(p.E * PFA), "r"(p.E * 32));
  const uint32_t eru = __reduce_max_sync(~0u, ering);
  const uint32_t zr = p.force_slow;
  uint32_t rk[4];
#pragma unroll
  for (int k = 0; k < 4; k++) rk[k] = (rq ^ (k * 32)) + lds32(A_MISC);
  uint32_t nd3, mk, ln, gl = 10, gc = 0;
  auto lane_id = []() { uint32_t l; asm volatile("mov.u32 %0, %%laneid;" : "=r"(l)); return l; };
  auto slot_node = [&](uint32_t l) { return __shfl_sync(~0u, nd3, ((l >> 2) & 6) | ((l >> 1) & 1)); };
  auto lswitch = [&]() {
    const uint32_t l = lane_id();
    TA = A_TAB + (ln ? (slot_node(l) >> gl) & 1023 : 384) * (CAP * 2) + ((l >> 1) & 2);
    if (ln) mk |= 32u << (ln & 255);
    else if (atoms_incp(A_MISC + 4, l == 0) == 31) {
      proxy_fence();
      mbar_expect(BAR_U, 16384);
      tma_load(A_TAB, tmb + TM_WH, 0, BAR_U); tma_load(A_TAB + 8192, tmb + TM_WH, 64, BAR_U);
    }
    __syncwarp();
    ln >>= 8; gl += 10;
  };
  auto pswitch = [&]() {
    const uint32_t l = lane_id(), nd = (nd3 >> gc) & 1023;
    const uint32_t a = ((l & 8) ? A_WD2 + (l & 7) * 144 : A_PT + nd * 128 + ((nd & 7) << 4)) ^ (l & 16);
#pragma unroll
    for (int k = 0; k < 4; k++) ldsm4t(PB[4 * k], PB[4 * k + 1], PB[4 * k + 2], PB[4 * k + 3], a ^ (k << 5));
    OP = lds16(A_POSH + __shfl_sync(~0u, nd, l >> 2) * 8 + (l & 3) * 2) * 0x10001;
  };
  auto flush = [&](int hf, uint32_t g) {
    const uint32_t l = lane_id(), nd = (nd3 >> g) & 1023, a = A_PT + nd * 128 + (((l >> 3) ^ (nd & 7)) << 4);
    stsm4(a ^ (hf << 6), MS[4 * hf], MS[4 * hf + 1], MS[4 * hf + 2], MS[4 * hf + 3]);
    if (hf) { sts16(A_POSH + __shfl_sync(~0u, nd, l >> 2) * 8 + (l & 3) * 2, hadd(U, U >> 16)); U = 0; }
#pragma unroll
    for (int j = 4 * hf; j < 4 * hf + 4; j++) MS[j] = 0;
  };
  auto look1 = [&]() { asm volatile("ld.volatile.shared.u16 %0, [%1];" : "=r"(tn) : "r"(TA) : "memory"); asm volatile("add.u32 %0, %0, 4;" : "+r"(TA)); };
  auto look2 = [&](uint32_t tn) {
    asm volatile("ld.volatile.shared.u32 %0, [%1];" : "=r"(rn) : "r"(A_IN + tn) : "memory");
    tt = __umulhi(tn, 3728271u) * p.EPC4 + (rn >> 16); rn &= 0xFFFF;
    if (ABL & 1) tt = (tt & 0x1FFFF) + 65536;
  };
  auto issue_q = [&](uint32_t rec) {
#pragma unroll
    for (int i = 0; i < 4; i++)
      if (ABL & 2) asm volatile("{.reg .b64 a; .reg .pred p, l; setp.eq.u32 p, %2, 0xFFFF; setp.ge.u32 l, %3, 8; mad.wide.u32 a, %2, 128, %1;\n @l cp.async.cg.shared.global [%0], [a], 16, p;}"
        :: "r"(dq + i * 128), "l"((i & 1) ? qp1 : qp0), "r"(__shfl_sync(~0u, rec, 2 * i, 8)), "r"(zr) : "memory");
      else asm volatile("{.reg .b64 a; .reg .pred p; setp.eq.u32 p, %2, 0xFFFF; mad.wide.u32 a, %2, 128, %1;\n cp.async.cg.shared.global [%0], [a], 16, p;}"
        :: "r"(dq + i * 128), "l"((i & 1) ? qp1 : qp0), "r"(__shfl_sync(~0u, rec, 2 * i, 8)) : "memory");
    asm volatile("cp.async.commit_group;" ::: "memory");
    dq ^= 2048;
  };
  auto issue_e = [&](uint32_t a, uint32_t rn, uint32_t tt) {
    if (ABL & 2) asm volatile("{.reg .b64 a; .reg .pred p, l; setp.eq.u32 p, %3, 0xFFFF; setp.ge.u32 l, %5, 8; mad.wide.u32 a, %2, 32, %1;\n @l cp.async.cg.shared.global.L2::cache_hint [%0], [a], 16, p, %4;}"
      :: "r"(a), "l"(epp), "r"(tt), "r"(rn), "l"(pol), "r"(zr) : "memory");
    else asm volatile("{.reg .b64 a; .reg .pred p; setp.eq.u32 p, %3, 0xFFFF; mad.wide.u32 a, %2, 32, %1;\n cp.async.cg.shared.global.L2::cache_hint [%0], [a], 16, p, %4;}"
      :: "r"(a), "l"(epp), "r"(tt), "r"(rn), "l"(pol) : "memory");
  };
  auto act = [&](const uint32_t* y, int k) {
#pragma unroll
    for (int i = 0; i < 4; i++) { m[4 * k + i] = hsilu(y[i]); MS[2 * k + (i >> 1)] = hadd(MS[2 * k + (i >> 1)], m[4 * k + i]); }
  };
  auto cfin = [&](uint32_t d) {
    uint32_t c0_ = 0, c1_ = 0;
#pragma unroll
    for (int k = 0; k < 4; k++) { const int kk = (VAR & 32) ? k : k ^ 2; hmma(c0_, c1_, m + 4 * kk, WX[2 * kk], WX[2 * kk + 1]); }
    U = hfma(__byte_perm(c0_, c1_, 0x5410), d, U);
  };
  auto events = [&]() {
    if (mk & 1) flush(1, gc - 10);
    if (mk & 2) { flush(0, gc); gc += 10; pswitch(); }
    if (mk & 32) lswitch();
    if (mk < 16) {
      const uint32_t l = lane_id(); int cta; asm volatile("mov.u32 %0, %%ctaid.x;" : "=r"(cta));
      rec = ((slot_node(l) >> (mk < 8 ? 20 : (l & 4) ? 10 : 0)) & 1023) + cta * p.NPC;
      if (rec >= p.N || (mk < 8 && (l & 4))) rec = 0xFFFF;
      qp0 = (uint64_t)p.h + (qp0 & 127); qp1 = qp0 ^ 16;
    }
  };
  auto step = [&](uint32_t st) {
    asm volatile("cp.async.wait_group 1;" ::: "memory");
    uint32_t E[4];
    ldsm4(E, re + eru);
#pragma unroll
    for (int k = 0; k < 4; k++) ldsm4(acc + 4 * k, rk[k] + st);
    look2(tn);
    issue_q(rec);
    issue_e(re + de, rn, tt); rec = rn;
    look1();
    re = __viaddmin_u32(re, -512, rtop);
    if (ABL & 4) { U ^= (E[0] ^ acc[0] ^ acc[4] ^ acc[8] ^ acc[12]) & zr; return; }
#pragma unroll
    for (int i = 0; i < 4; i++) A1[i] = pack_f16(__uint_as_float(__byte_perm(E[i], 0, 0x1044)), bf_hi(E[i]));
    const uint32_t Sa = decode(acc[0], acc[2], acc[4], acc[6]), Sb = decode(acc[1], acc[3], acc[5], acc[7]);
    const uint32_t Dp = D;
    D = hsub(OP, __byte_perm(Sa, Sb, 0x6420));
    const __half2 d = *(const __half2*)&D, x = __hmul2(d, d), y = __hmul2(__high2half2(d), __high2half2(d));
    A2[2] = *(const uint32_t*)&x; A2[3] = *(const uint32_t*)&y;
    if (VAR & 1) yh[4] |= A1[3] & zr;
    if (VAR & 2) yh[6] |= A2[3] & zr;
    act(yh, 2); act(yh + 4, 3);
#pragma unroll
    for (int j = 0; j < 8; j++) { hmma(acc[2 * j], acc[2 * j + 1], A1, W3[2 * j], W3[2 * j + 1]); hmma(acc[2 * j], acc[2 * j + 1], A2, PB[2 * j], PB[2 * j + 1]); }
    if (VAR & 4) m[(VAR & 32) ? 0 : 8] |= acc[0] & zr;
    cfin(Dp);
    if (VAR & 8) acc[6] |= acc[14] & zr;
    if (VAR & 16) acc[7] |= acc[10] & zr;
    if (VAR & 64) acc[5] |= acc[8] & zr;
    if (VAR & 128) acc[3] |= tt & zr;
    if (VAR & 256) acc[6] |= U & zr;
    if (VAR & 512) acc[2] |= m[15] & zr;
    if (VAR & 1024) acc[4] |= acc[12] & zr;
    act(acc, 0); act(acc + 4, 1);
#pragma unroll
    for (int i = 0; i < 8; i++) yh[i] = acc[8 + i];
  };
#pragma unroll
  for (int i = 0; i < 8; i++) { m[i] = 0; yh[i] = 0; MS[i] = 0; A1[i & 3] = 0; }
  { const uint32_t sc = p.sched[wid], g0 = sc & 63, g1 = (sc >> 6) & 63, g2 = sc >> 12;
    TA = A_TAB + lds16(A_ROWS + g0 * 16 + oc * 4 + (lane & 2)) * (CAP * 2) + ((lane >> 1) & 2);
    nd3 = lds16(A_ROWS + g0 * 16 + r7 * 2) | (lds16(A_ROWS + g1 * 16 + r7 * 2) << 10) | (lds16(A_ROWS + g2 * 16 + r7 * 2) << 20);
    ln = __reduce_max_sync(~0u, lds32(A_LEN + g0 * 4) | (lds32(A_LEN + g1 * 4) << 8) | (lds32(A_LEN + g2 * 4) << 16));
    mk = 2u << max(ln & 255, 4u); ln >>= 8;
    uint32_t t3[3], ra, rb;
#pragma unroll
    for (int k = 0; k < 3; k++) { look1(); t3[k] = tn; }
    look1();
    look2(t3[0]); ra = rn; const uint32_t ta = tt;
    look2(t3[1]); rb = rn; const uint32_t tb = tt;
    look2(t3[2]);
    issue_e(re + de, ra, ta); issue_e(re + de - 512, rb, tb);
    mbar_wait(BAR_Q, 0);
    STAMP(8);
    issue_q(ra);
    pswitch();
    issue_q(rb); issue_e(re + de - 1024, rn, tt); rec = rn;
  }
  sl = 2048;
#pragma unroll 1
  do {
    if ((mk & 35) || mk < 16) events();
    sl ^= 2048; asm volatile("shr.u32 %0, %0, 1;" : "+r"(mk)); step(sl);
  } while (mk >= 4);
  sl += lds32(A_MISC); rq = rk[0] + lds32(A_MISC); dq = (dq + lds32(A_MISC)) & ~2048u;
  if (mk & 1) flush(1, gc - 10);
  STAMP(9);
  {
    int cta; asm volatile("mov.u32 %0, %%ctaid.x;" : "=r"(cta));
    const uint32_t l = lane_id(), node0 = cta * p.NPC; const int nloc = min(p.NPC, p.N - (int)node0);
    constexpr uint64_t dW = DHI | (A_TAB >> 4);
    float y1[32], y2[32];
    uint32_t H[16], po[3];
    asm volatile("cp.async.wait_group 1;" ::: "memory");
    __syncwarp();
    { const uint32_t nd = (nd3 >> ((l & 8) ? 10 : 0)) & 1023, a = A_PT + nd * 128 + (((l >> 4) ^ (nd & 7)) << 4);
#pragma unroll
      for (int k = 0; k < 4; k++) { ldsm4(acc + 4 * k, a ^ (k << 5)); ldsm4(H + 4 * k, (rq ^ (k * 32)) + (sl ^ 2048)); } }
    mbar_wait(BAR_U, 0);
    STAMP(10);
    wg_fence();
    rh64<0>(y1, acc, dW + 512); rh64<1>(y1, acc + 4, dW + 640); rh64<1>(y1, acc + 8, dW + 768); rh64<1>(y1, acc + 12, dW + 896);
    rs64<1>(y1, H, dW); rs64<1>(y1, H + 4, dW + 128); rs64<1>(y1, H + 8, dW + 256); rs64<1>(y1, H + 12, dW + 384);
    wg_commit();
    act(yh, 2); act(yh + 4, 3); cfin(D);
    sts16(A_POSH + (__shfl_sync(~0u, nd3, l >> 2) >> 20) * 8 + (l & 3) * 2, hadd(U, U >> 16));
    __syncwarp();
    if (l == 0) mbar_arrive(BAR_A);
    asm volatile("cp.async.wait_group 0;" ::: "memory");
    __syncwarp();
    wg_wait0(); fence_regs(y1);
#pragma unroll
    for (int k = 0; k < 4; k++) ldsm4(H + 4 * k, (rq ^ (k * 32)) + sl);
#pragma unroll
    for (int j = 0; j < 8; j++) acc[2 * j] = MS[j];
    wg_fence();
    rh64<0>(y2, acc, dW + 512); rh64<1>(y2, acc + 4, dW + 640); rh64<1>(y2, acc + 8, dW + 768); rh64<1>(y2, acc + 12, dW + 896);
    rs64<1>(y2, H, dW); rs64<1>(y2, H + 4, dW + 128); rs64<1>(y2, H + 8, dW + 256); rs64<1>(y2, H + 12, dW + 384);
    wg_commit();
    const float ov = y1[0] * y1[2];
    auto fin = [&](uint32_t x, float a, float b) { return badd(x, pack_bf16(silu(a), silu(b))); };
#pragma unroll
    for (int k = 0; k < 4; k += 2) {
      const uint32_t a = (rq ^ (k * 32)) + (sl ^ 2048); uint32_t x[8];
      ldsm4(x, a); ldsm4(x + 4, a ^ 32);
#pragma unroll
      for (int j = 0; j < 8; j++) x[j] = fin(x[j], y1[8 * k + 2 * j], y1[8 * k + 2 * j + 1]);
      stsm4(a, x[0], x[1], x[2], x[3]); stsm4(a ^ 32, x[4], x[5], x[6], x[7]);
    }
    { const uint32_t n0 = __shfl_sync(~0u, nd3, (l >> 2) & 6), n1 = __shfl_sync(~0u, nd3, ((l >> 2) & 6) | 1);
#pragma unroll
      for (int g = 0; g < 3; g++) po[g] = ((n0 >> (10 * g)) & 1023) | (((n1 >> (10 * g)) & 1023) << 16); }
    const uint64_t ob = (uint64_t)(p.out + (size_t)node0 * 64) + (((l & 7) ^ ((l >> 2) & 6)) << 4);
    auto put = [&](uint32_t a, uint32_t nn) {
      uint32_t v[8]; lds128(v, a); lds128(v + 4, a + 128);
#pragma unroll
      for (int i = 0; i < 2; i++)
        asm volatile("{.reg .pred p; .reg .b64 a; setp.lt.s32 p, %0, %1; mad.wide.u32 a, %0, 128, %2; @p st.global.v4.u32 [a], {%3,%4,%5,%6};}"
          :: "r"(i ? nn >> 16 : nn & 0xFFFF), "r"(nloc), "l"(ob ^ (i << 4)), "r"(v[4 * i]), "r"(v[4 * i + 1]), "r"(v[4 * i + 2]), "r"(v[4 * i + 3]) : "memory");
    };
    wg_wait0(); fence_regs(y2);
    __syncwarp();
    put(dq + (sl ^ 2048), po[0]); put(dq + 256 + (sl ^ 2048), po[1]);
    bool bad = !(fabsf(ov * y2[0] * 0.f) < 1.f);
#pragma unroll
    for (int j = 0; j < 16; j += 2) H[j] = fin(H[j], y2[2 * j], y2[2 * j + 1]);
#pragma unroll
    for (int k = 0; k < 4; k++) stsm4((rq ^ (k * 32)) + sl, H[4 * k], H[4 * k + 1], H[4 * k + 2], H[4 * k + 3]);
    __syncwarp();
    put(dq + sl, po[2]);
    const uint32_t c = __shfl_sync(~0u, atoms_incp(A_MISC + 8, l == 0), 0);
    if (c < 6) {
      mbar_wait(BAR_A, 0);
      uint32_t x[6];
#pragma unroll
      for (int k = 0; k < 6; k++) {
        const uint32_t i = c * 192 + k * 32 + l, u = lds16(A_POSH + i * 2 + i / 3 * 2);
        bad |= (u & 0x7C00) == 0x7C00;
        x[k] = pack_bf16(fmaf(__half2float(__ushort_as_half(u)), __uint_as_float(lds32(A_MISC + 12)), bf_lo(lds16(A_POSB + i * 2))), 0.f);
      }
      uint16_t* op = p.out + (size_t)p.N * 64 + (size_t)node0 * 3 + c * 192 + l;
#pragma unroll
      for (int k = 0; k < 6; k++)
        asm volatile("{.reg .pred p; setp.lt.s32 p, %0, %1; @p st.global.u16 [%2], %3;}" :: "r"(c * 192 + k * 32 + l), "r"(nloc * 3), "l"(op + k * 32), "h"((uint16_t)x[k]) : "memory");
    }
    if (__syncthreads_or(bad) && !ABL) { slow_path(p); return; }
  }
  STAMP(11);
}

}

typedef CUresult (*EncodeFn)(CUtensorMap*, CUtensorMapDataType, cuuint32_t, void*, const cuuint64_t*, const cuuint64_t*, const cuuint32_t*, const cuuint32_t*,
                             CUtensorMapInterleave, CUtensorMapSwizzle, CUtensorMapL2promotion, CUtensorMapFloatOOBfill);

extern "C" void kernel_launch(void* const* d_in, const int* in_sizes, int n_in, void* d_out, int out_size) {
  Params p; Maps maps;
  p.h = (const uint16_t*)d_in[0]; p.pos = (const uint16_t*)d_in[1]; p.ea = (const uint16_t*)d_in[2];
  p.src = (const int*)d_in[3]; p.dst = (const int*)d_in[4];
  p.we = (const uint16_t*)d_in[5]; p.wx = (const uint16_t*)d_in[6]; p.wh = (const uint16_t*)d_in[7];
  p.out = (uint16_t*)d_out;
  p.N = in_sizes[0] / 64; p.E = in_sizes[3];
  p.NPC = (p.N + G - 1) / G;
  p.EPC = ((p.E + G * 4 - 1) / (G * 4)) * 4;
  p.magic = (uint32_t)((1ull << 32) / (uint64_t)p.NPC) + 1;
  const uint32_t scheds[7][16] = {
    {0x28784, 0x2560a, 0x27548, 0x2b4c7, 0x2c2c9, 0x1f64c, 0x1b5d4, 0x22805, 0x2148d, 0x29742, 0x2fb80, 0x2d701, 0x2a406, 0x1a58f, 0x248c3, 0x2644e},
    {0x27787, 0x1f512, 0x25706, 0x2e741, 0x2fb40, 0x2938a, 0x2354d, 0x2a405, 0x2b802, 0x24883, 0x264c9, 0x1b60c, 0x2c584, 0x1a64b, 0x2144f, 0x285c8},
    {0x2e781, 0x258c3, 0x2b587, 0x247c6, 0x2148e, 0x20510, 0x2754f, 0x264cb, 0x2d602, 0x1d70d, 0x2fb00, 0x22645, 0x2a309, 0x1b68a, 0x285c4, 0x29448},
    {0x2758d, 0x26608, 0x2b5c6, 0x2d801, 0x2fb80, 0x1e513, 0x2a545, 0x1c64a, 0x2838c, 0x24883, 0x2544b, 0x293c7, 0x2c7c2, 0x1b490, 0x1d689, 0x23844},
    {0x2e543, 0x23608, 0x2c5c4, 0x26646, 0x2548e, 0x2a30a, 0x2858d, 0x2450b, 0x299c1, 0x2b7c2, 0x2fb40, 0x1b4d0, 0x21449, 0x22745, 0x20787, 0x1c68f},
    {0x299c2, 0x1d68d, 0x2a38a, 0x2f2c3, 0x2eb00, 0x2640c, 0x257c6, 0x28448, 0x22807, 0x2d841, 0x1c552, 0x2b504, 0x1e5d6, 0x234c9, 0x24645, 0x1b60f},
    {0x27449, 0x23786, 0x263cc, 0x29941, 0x2a604, 0x245cd, 0x2b7c3, 0x20510, 0x21747, 0x2c642, 0x2fb40, 0x1b68a, 0x2e2c5, 0x1c4d2, 0x28588, 0x2254e}};
  const uint32_t* sched = scheds[SCH];
  for (int i = 0; i < 16; i++) p.sched[i] = sched[i];
  p.EPC4 = p.EPC * 4;
  uint64_t al = (uint64_t)d_out;
  for (int i = 0; i < 8; i++) if (i != 1) al |= (uint64_t)d_in[i];
  p.force_slow = (al & 127) || (p.E & 3) || p.NPC > 384 || p.NPC < 2 || p.EPC > 6144;
  cudaGetSymbolAddress((void**)&p.s, g_s);
  void* fn = nullptr; cudaDriverEntryPointQueryResult qr;
  cudaGetDriverEntryPoint("cuTensorMapEncodeTiled", &fn, cudaEnableDefault, &qr);
  auto mk = [&](CUtensorMap* tm, void* base, int rows, int box) {
    const cuuint64_t dim[2] = {64, (cuuint64_t)rows}, str[1] = {128}; const cuuint32_t bx[2] = {64, (cuuint32_t)box}, es[2] = {1, 1};
    ((EncodeFn)fn)(tm, CU_TENSOR_MAP_DATA_TYPE_BFLOAT16, 2, base, dim, str, bx, es, CU_TENSOR_MAP_INTERLEAVE_NONE, CU_TENSOR_MAP_SWIZZLE_128B,
                   CU_TENSOR_MAP_L2_PROMOTION_NONE, CU_TENSOR_MAP_FLOAT_OOB_FILL_NONE);
  };
  mk(&maps.m[TM_H / 128], d_in[0], p.N, 64); mk(&maps.m[TM_WE / 128], d_in[5], 145, 64); mk(&maps.m[TM_WH / 128], p.s->wh, 128, 64);
  mk(&maps.m[TM_Q / 128], p.s->q, p.N, 64);
  mk(&maps.m[TM_W3 / 128], d_in[5], 145, 16);
  for (int k = 0; k < 2; k++) {
    const cuuint64_t dim[2] = {(cuuint64_t)G * (192 >> k), (cuuint64_t)G}, str[1] = {(cuuint64_t)G * FS}; const cuuint32_t bx[2] = {64, G}, es[2] = {1, 1};
    ((EncodeFn)fn)(&maps.m[TM_XA / 128 + k], k ? CU_TENSOR_MAP_DATA_TYPE_UINT32 : CU_TENSOR_MAP_DATA_TYPE_UINT16, 2, p.s->x, dim, str, bx, es, CU_TENSOR_MAP_INTERLEAVE_NONE,
                   CU_TENSOR_MAP_SWIZZLE_NONE, CU_TENSOR_MAP_L2_PROMOTION_NONE, CU_TENSOR_MAP_FLOAT_OOB_FILL_NONE);
  }
  cudaFuncSetAttribute(egnn_kernel, cudaFuncAttributeMaxDynamicSharedMemorySize, SMEM);
  egnn_kernel<<<G, NT, SMEM>>>(p, maps);
}
```

```cpp
#include <cuda_runtime.h>
#include <cuda_bf16.h>
#include <cuda_fp16.h>
#include <cuda.h>
#include <stdint.h>

#define SCH 3
#define PFA 6
#define PL 0
#define T3 0
#define FR 2
#define XD 0
#define WIN 6
namespace {

constexpr int G = 132;
constexpr int NT = 512;
constexpr int CAP = 48;
constexpr int FS = 384;
constexpr int BS = 1152;
constexpr uint32_t sb = 1024;

constexpr uint32_t A_RING = sb;
constexpr uint32_t A_PT = A_RING + 16 * 5120;
constexpr uint32_t A_W3 = A_PT + 49152;
constexpr uint32_t A_TAB = A_W3 + 2048;
constexpr uint32_t A_IN = A_TAB + 37888;
constexpr uint32_t A_WD = A_IN + G * FS + 512;
constexpr uint32_t A_WD2 = A_WD + 256;
constexpr uint32_t A_BAR = A_WD2 + 1024;
constexpr uint32_t A_MISC = A_BAR + 160;
constexpr uint32_t A_DH = A_MISC + 16;
constexpr uint32_t A_CNT = A_DH + 256;
constexpr uint32_t A_POSH = A_CNT + 2176;
constexpr uint32_t A_POSB = A_POSH + 3072;
constexpr uint32_t A_ROWS = A_POSB + 2304;
constexpr uint32_t A_LEN = A_ROWS + 768;
constexpr uint32_t A_END = A_LEN + 192;
constexpr uint32_t A_XC = A_TAB + 385 * CAP * 2, A_TRASH = A_XC + 144;
constexpr uint32_t A_E3 = A_IN + G / 4 * BS;
constexpr uint32_t A_WHS = A_PT - 128;
constexpr int SMEM = A_END - sb;
static_assert(SMEM <= 232448 && A_TAB % 1024 == 0 && A_IN % 1024 == 0 && A_PT % 1024 == 0 && A_WD2 % 128 == 0 && A_ROWS % 16 == 0, "smem");
constexpr int NX = 384, CH = NX * 16;
constexpr uint32_t A_QS = A_RING, A_W = A_QS + 49152, A_SA = A_IN, A_SB = A_SA + (G + 1) * 128, A_SRC = A_TAB;
__host__ __device__ constexpr uint32_t a_dst(int k) { return k < 2 ? A_W + 16384 + k * CH : A_SRC + (k + 2) * CH; }
static_assert(a_dst(1) + CH <= A_PT && a_dst(3) + CH <= A_IN && A_SB + (G + 1) * 256 <= A_WD, "staging");
constexpr uint32_t BAR_C = A_BAR, BAR_T = BAR_C + 64, BAR_W = A_BAR + 112, BAR_U = A_BAR + 120, BAR_Q = A_BAR + 128, BAR_X = A_BAR + 136, BAR_A = A_BAR + 144;

#define ABL 0
#define VAR 608
#define HW0 4
constexpr int NREP = 8;
struct Scratch {
  uint4 q[(G * 384 + 64) * 8];
  uint4 x[G * G * 24];
  uint2 xe[G * G * 32];
  uint32_t wh[128 * 32];
  uint32_t ep[G * 32];
  uint32_t cnt[NREP * 32];
};
__device__ __align__(256) Scratch g_s;
#define STAMP(k)

struct Maps { CUtensorMap m[7]; };
constexpr int TM_H = 0, TM_WE = 128, TM_WH = 256, TM_Q = 384, TM_XA = 512, TM_XB = 640, TM_W3 = 768;
struct Params {
  const int* dst; const int* src; int E, EPC, force_slow, NPC; Scratch* s; int N; uint32_t magic;
  const uint16_t* h; const uint16_t* pos; const uint16_t* ea; const uint16_t* we; const uint16_t* wx; const uint16_t* wh; uint16_t* out;
  uint32_t EPC4, sched[16];
};

#define R32(d) "+f"(d[0]),"+f"(d[1]),"+f"(d[2]),"+f"(d[3]),"+f"(d[4]),"+f"(d[5]),"+f"(d[6]),"+f"(d[7]),"+f"(d[8]),"+f"(d[9]),"+f"(d[10]),"+f"(d[11]),"+f"(d[12]),"+f"(d[13]),"+f"(d[14]),"+f"(d[15]),"+f"(d[16]),"+f"(d[17]),"+f"(d[18]),"+f"(d[19]),"+f"(d[20]),"+f"(d[21]),"+f"(d[22]),"+f"(d[23]),"+f"(d[24]),"+f"(d[25]),"+f"(d[26]),"+f"(d[27]),"+f"(d[28]),"+f"(d[29]),"+f"(d[30]),"+f"(d[31])
#define S32 "{%0,%1,%2,%3,%4,%5,%6,%7,%8,%9,%10,%11,%12,%13,%14,%15,%16,%17,%18,%19,%20,%21,%22,%23,%24,%25,%26,%27,%28,%29,%30,%31}"
#define R16(d) "+f"(d[0]),"+f"(d[1]),"+f"(d[2]),"+f"(d[3]),"+f"(d[4]),"+f"(d[5]),"+f"(d[6]),"+f"(d[7]),"+f"(d[8]),"+f"(d[9]),"+f"(d[10]),"+f"(d[11]),"+f"(d[12]),"+f"(d[13]),"+f"(d[14]),"+f"(d[15])
#define S16 "{%0,%1,%2,%3,%4,%5,%6,%7,%8,%9,%10,%11,%12,%13,%14,%15}"
#define DI __device__ __forceinline__

constexpr uint64_t DHI = (64ull << 32) | (1ull << 62);
template<int SD> DI void ss64(float (&d)[32], uint64_t da, uint64_t db) {
  asm volatile("wgmma.mma_async.sync.aligned.m64n64k16.f32.bf16.bf16 " S32 ", %32, %33, %34, 1, 1, 0, 1;" : R32(d) : "l"(da), "l"(db), "n"(SD)); }
template<int SD> DI void rs64(float (&d)[32], const uint32_t* a, uint64_t db) {
  asm volatile("wgmma.mma_async.sync.aligned.m64n64k16.f32.bf16.bf16 " S32 ", {%32,%33,%34,%35}, %36, %37, 1, 1, 1;" : R32(d) : "r"(a[0]), "r"(a[1]), "r"(a[2]), "r"(a[3]), "l"(db), "n"(SD)); }
template<int SD> DI void rh64(float (&d)[32], const uint32_t* a, uint64_t db) {
  asm volatile("wgmma.mma_async.sync.aligned.m64n64k16.f32.f16.f16 " S32 ", {%32,%33,%34,%35}, %36, %37, 1, 1, 1;" : R32(d) : "r"(a[0]), "r"(a[1]), "r"(a[2]), "r"(a[3]), "l"(db), "n"(SD)); }
DI void wg_fence() { asm volatile("wgmma.fence.sync.aligned;" ::: "memory"); }
DI void wg_commit() { asm volatile("wgmma.commit_group.sync.aligned;" ::: "memory"); }
DI void wg_wait0() { asm volatile("wgmma.wait_group.sync.aligned 0;" ::: "memory"); }
DI void fence_regs(float (&d)[32]) { asm volatile("" : R32(d) :: "memory"); }
DI void fence_regs(float (&d)[16]) { asm volatile("" : R16(d) :: "memory"); }
DI void proxy_fence() { asm volatile("fence.proxy.async.shared::cta;" ::: "memory"); }
DI void hmma(uint32_t& d0, uint32_t& d1, const uint32_t* a, uint32_t b0, uint32_t b1) {
  asm("mma.sync.aligned.m16n8k16.row.col.f16.f16.f16.f16 {%0,%1}, {%2,%3,%4,%5}, {%6,%7}, {%0,%1};" : "+r"(d0), "+r"(d1) : "r"(a[0]), "r"(a[1]), "r"(a[2]), "r"(a[3]), "r"(b0), "r"(b1)); }
DI uint64_t pol_first() { uint64_t r; asm("createpolicy.fractional.L2::evict_first.b64 %0, 1.0;" : "=l"(r)); return r; }
DI float tanh_ap(float x) { float y; asm("tanh.approx.f32 %0, %1;" : "=f"(y) : "f"(x)); return y; }
DI float silu(float y) { return fmaf(y, tanh_ap(y), y); }
DI uint32_t pack_bf16(float lo, float hi) { uint32_t r; asm("cvt.rn.bf16x2.f32 %0, %1, %2;" : "=r"(r) : "f"(hi), "f"(lo)); return r; }
DI uint32_t pack_f16(float lo, float hi) { uint32_t r; asm("cvt.rn.f16x2.f32 %0, %1, %2;" : "=r"(r) : "f"(hi), "f"(lo)); return r; }
DI float bf_lo(uint32_t v) { return __uint_as_float(v << 16); }
DI float bf_hi(uint32_t v) { return __uint_as_float(v & 0xFFFF0000u); }
DI uint32_t b2h(uint32_t v) { return pack_f16(bf_lo(v), bf_hi(v)); }
DI uint32_t h2b(uint32_t v) { const float2 f = __half22float2(*(const __half2*)&v); return pack_bf16(f.x, f.y); }
DI uint32_t hadd(uint32_t a, uint32_t b) { uint32_t r; asm("add.rn.f16x2 %0, %1, %2;" : "=r"(r) : "r"(a), "r"(b)); return r; }
DI uint32_t hsub(uint32_t a, uint32_t b) { uint32_t r; asm("sub.rn.f16x2 %0, %1, %2;" : "=r"(r) : "r"(a), "r"(b)); return r; }
DI uint32_t hfma(uint32_t a, uint32_t b, uint32_t c) { uint32_t r; asm("fma.rn.f16x2 %0, %1, %2, %3;" : "=r"(r) : "r"(a), "r"(b), "r"(c)); return r; }
DI uint32_t hsilu(uint32_t y) { uint32_t t; asm("tanh.approx.f16x2 %0, %1;" : "=r"(t) : "r"(y)); return hfma(y, t, y); }
DI uint32_t badd(uint32_t a, uint32_t b) { uint32_t r; asm("add.rn.bf16x2 %0, %1, %2;" : "=r"(r) : "r"(a), "r"(b)); return r; }
DI uint32_t bhalf(uint32_t v) { uint32_t r; asm("mul.rn.bf16x2 %0, %1, %2;" : "=r"(r) : "r"(v), "r"(0x3F003F00u)); return r; }
DI uint32_t amax2(uint32_t mx, uint32_t v) { return __vmaxu2(mx, v & 0x7FFF7FFFu); }
DI uint32_t amax_warp(uint32_t mx) { return __reduce_max_sync(~0u, max(mx & 0xFFFF, mx >> 16)); }
DI uint32_t decode(uint32_t a, uint32_t b, uint32_t c, uint32_t d) {
  if (XD) return a ^ __funnelshift_l(b, b, 2) ^ __funnelshift_l(c, c, 4) ^ __funnelshift_l(d, d, 6);
  return a + b * 4 + c * 16 + d * 64;
}
DI void mbar_wait(uint32_t bar, uint32_t parity) {
  asm volatile("{.reg .pred p; .reg .u32 c; mov.u32 c, 0;\n"
    "LW_%=: mbarrier.try_wait.parity.shared::cta.b64 p, [%0], %1;\n"
    "@p bra.uni LD_%=;\n add.u32 c, c, 1; setp.lt.u32 p, c, 20000000;\n @p bra.uni LW_%=;\n LD_%=:}" :: "r"(bar), "r"(parity) : "memory");
}
DI void mbar_arrive(uint32_t bar) { asm volatile("mbarrier.arrive.shared::cta.b64 _, [%0];" :: "r"(bar) : "memory"); }
DI void bar_sync(int id, int n) { asm volatile("bar.sync %0, %1;" :: "r"(id), "r"(n) : "memory"); }
DI void bar_arrive(int id, int n) { asm volatile("bar.arrive %0, %1;" :: "r"(id), "r"(n) : "memory"); }
DI void sts128(uint32_t a, uint32_t x, uint32_t y, uint32_t z, uint32_t w) { asm volatile("st.shared.v4.u32 [%0], {%1,%2,%3,%4};" :: "r"(a), "r"(x), "r"(y), "r"(z), "r"(w) : "memory"); }
DI void sts64(uint32_t a, uint32_t x, uint32_t y) { asm volatile("st.shared.v2.u32 [%0], {%1,%2};" :: "r"(a), "r"(x), "r"(y) : "memory"); }
DI void sts32(uint32_t a, uint32_t x) { asm volatile("st.shared.u32 [%0], %1;" :: "r"(a), "r"(x) : "memory"); }
DI void sts16(uint32_t a, uint32_t x) { asm volatile("st.shared.u16 [%0], %1;" :: "r"(a), "h"((uint16_t)x) : "memory"); }
DI void sts32p(uint32_t a, uint32_t x, bool p) { asm volatile("{.reg .pred p; setp.ne.b32 p, %2, 0; @p st.shared.u32 [%0], %1;}" :: "r"(a), "r"(x), "r"((int)p) : "memory"); }
DI void sts16p(uint32_t a, uint32_t x, bool p) { asm volatile("{.reg .pred p; setp.ne.b32 p, %2, 0; @p st.shared.u16 [%0], %1;}" :: "r"(a), "h"((uint16_t)x), "r"((int)p) : "memory"); }
DI void lds128(uint32_t* v, uint32_t a) { asm volatile("ld.shared.v4.u32 {%0, %1, %2, %3}, [%4];" : "=r"(v[0]), "=r"(v[1]), "=r"(v[2]), "=r"(v[3]) : "r"(a) : "memory"); }
DI void lds64(uint32_t& x, uint32_t& y, uint32_t a) { asm volatile("ld.shared.v2.u32 {%0, %1}, [%2];" : "=r"(x), "=r"(y) : "r"(a) : "memory"); }
DI uint32_t lds32(uint32_t a) { uint32_t x; asm volatile("ld.shared.u32 %0, [%1];" : "=r"(x) : "r"(a) : "memory"); return x; }
DI uint32_t lds16(uint32_t a) { uint32_t x; asm volatile("ld.shared.u16 %0, [%1];" : "=r"(x) : "r"(a) : "memory"); return x; }
DI uint32_t atoms_add(uint32_t a, uint32_t v) { uint32_t r; asm volatile("atom.shared.add.u32 %0, [%1], %2;" : "=r"(r) : "r"(a), "r"(v) : "memory"); return r; }
DI uint32_t atoms_incp(uint32_t a, bool p) { uint32_t r = 0; asm volatile("{.reg .pred p; setp.ne.b32 p, %2, 0; @p atom.shared.add.u32 %0, [%1], 1;}" : "+r"(r) : "r"(a), "r"((int)p) : "memory"); return r; }
DI uint32_t ldg_poll(const void* a) { uint32_t x; asm volatile("ld.relaxed.gpu.global.u32 %0, [%1];" : "=r"(x) : "l"(a) : "memory"); return x; }
DI uint2 ldg_poll2(const void* a) { uint2 x; asm volatile("ld.relaxed.gpu.global.v2.u32 {%0, %1}, [%2];" : "=r"(x.x), "=r"(x.y) : "l"(a) : "memory"); return x; }
DI void bulk_load(uint32_t dst, const void* src, uint32_t bytes, uint32_t bar) {
  asm volatile("cp.async.bulk.shared::cluster.global.mbarrier::complete_tx::bytes.L2::cache_hint [%0], [%1], %2, [%3], %4;" :: "r"(dst), "l"(src), "r"(bytes), "r"(bar), "l"(pol_first()) : "memory"); }
DI void mbar_expect(uint32_t bar, uint32_t bytes) { asm volatile("mbarrier.arrive.expect_tx.shared::cta.b64 _, [%0], %1;" :: "r"(bar), "r"(bytes) : "memory"); }
DI void mbar_init(uint32_t bar, int n) { asm volatile("mbarrier.init.shared::cta.b64 [%0], %1;" :: "r"(bar), "r"(n) : "memory"); }
DI void tma_load(uint32_t dst, uint64_t tm, int row, uint32_t bar) {
  asm volatile("cp.async.bulk.tensor.2d.shared::cluster.global.mbarrier::complete_tx::bytes.L2::cache_hint [%0], [%1, {%3, %4}], [%2], %5;" :: "r"(dst), "l"(tm), "r"(bar), "r"(0), "r"(row), "l"(pol_first()) : "memory"); }
DI void tma_store(uint64_t tm, int col, int row, uint32_t src) {
  asm volatile("cp.async.bulk.tensor.2d.global.shared::cta.bulk_group [%0, {%2, %3}], [%1];" :: "l"(tm), "r"(src), "r"(col), "r"(row) : "memory"); }
DI void bulk_commit() { asm volatile("cp.async.bulk.commit_group;" ::: "memory"); }
DI void stsm4(uint32_t a, uint32_t x, uint32_t y, uint32_t z, uint32_t w) { asm volatile("stmatrix.sync.aligned.m8n8.x4.shared.b16 [%0], {%1,%2,%3,%4};" :: "r"(a), "r"(x), "r"(y), "r"(z), "r"(w) : "memory"); }
DI void ldsm4(uint32_t* v, uint32_t a) { asm volatile("ldmatrix.sync.aligned.m8n8.x4.shared.b16 {%0,%1,%2,%3}, [%4];" : "=r"(v[0]), "=r"(v[1]), "=r"(v[2]), "=r"(v[3]) : "r"(a) : "memory"); }
DI void ldsm4t(uint32_t& x, uint32_t& y, uint32_t& z, uint32_t& w, uint32_t a) { asm volatile("ldmatrix.sync.aligned.m8n8.x4.trans.shared.b16 {%0,%1,%2,%3}, [%4];" : "=r"(x), "=r"(y), "=r"(z), "=r"(w) : "r"(a) : "memory"); }

__device__ __noinline__ void slow_path(const Params& p) {
  const int lane = threadIdx.x & 31, wid = threadIdx.x >> 5;
  const uint32_t ab = sb + wid * (24 * 528);
  const uint32_t* we = (const uint32_t*)p.we;
  const int nend = min(p.N, (blockIdx.x + 1) * p.NPC);
  auto rowmul = [&](uint32_t hv, const uint32_t* w, float& y0, float& y1) {
#pragma unroll 4
    for (int k = 0; k < 32; k++) {
      const uint32_t hk = __shfl_sync(~0u, hv, k), wa = __ldg(w + 2 * k * 32 + lane), wb = __ldg(w + (2 * k + 1) * 32 + lane);
      y0 = fmaf(bf_lo(hk), bf_lo(wa), fmaf(bf_hi(hk), bf_lo(wb), y0)); y1 = fmaf(bf_lo(hk), bf_hi(wa), fmaf(bf_hi(hk), bf_hi(wb), y1));
    }
  };
  auto act = [](float x) { return x / (1.f + __expf(-x)); };
  auto hrow = [&](int n) { return __ldg(p.h + (size_t)n * 64 + 2 * lane) | ((uint32_t)__ldg(p.h + (size_t)n * 64 + 2 * lane + 1) << 16); };
  const uint32_t wdv = __ldg(we + 128 * 32 + lane), wxv = __ldg((const uint32_t*)p.wx + lane);
  for (int nb = blockIdx.x * p.NPC + wid * 24; nb < nend; nb += 384) {
    const int cnt = min(24, nend - nb);
    for (int n = 0; n < cnt; n++) {
      float y0 = 0.f, y1 = 0.f; rowmul(hrow(nb + n), we, y0, y1);
      sts64(ab + n * 528 + lane * 8, 0, 0); sts64(ab + n * 528 + 256 + lane * 8, __float_as_uint(y0), __float_as_uint(y1));
      if (lane < 4) sts32(ab + n * 528 + 512 + lane * 4, 0);
    }
    __syncwarp();
    for (int base = 0; base < p.E; base += 32) {
      const uint32_t dl = base + lane < p.E ? (uint32_t)(__ldg(p.dst + base + lane) - nb) : 0xFFFFFFFFu;
      uint32_t mk = __ballot_sync(~0u, dl < (uint32_t)cnt);
      while (mk) {
        const int l = __ffs(mk) - 1; mk &= mk - 1;
        const int e = base + l, n = __shfl_sync(~0u, dl, l), s = __ldg(p.src + e);
        const uint32_t a = ab + n * 528;
        float df = 0.f;
        if (lane < 3) df = bf_lo(pack_bf16(bf_lo(__ldg(p.pos + (size_t)(nb + n) * 3 + lane)) - bf_lo(__ldg(p.pos + (size_t)s * 3 + lane)), 0.f));
        float d2 = df * df; d2 += __shfl_xor_sync(~0u, d2, 1); d2 += __shfl_xor_sync(~0u, d2, 2); d2 = __shfl_sync(~0u, d2, 0);
        uint32_t x0, x1; lds64(x0, x1, a + 256 + lane * 8);
        float y0 = fmaf(d2, bf_lo(wdv), __uint_as_float(x0)), y1 = fmaf(d2, bf_hi(wdv), __uint_as_float(x1));
        rowmul(hrow(s), we + 64 * 32, y0, y1);
        for (int k = 0; k < 16; k++) { const float ev = bf_lo(__ldg(p.ea + (size_t)e * 16 + k)); const uint32_t w = __ldg(we + (129 + k) * 32 + lane); y0 = fmaf(ev, bf_lo(w), y0); y1 = fmaf(ev, bf_hi(w), y1); }
        y0 = act(y0); y1 = act(y1);
        float c = y0 * bf_lo(wxv) + y1 * bf_hi(wxv);
#pragma unroll
        for (int o = 16; o; o >>= 1) c += __shfl_xor_sync(~0u, c, o);
        lds64(x0, x1, a + lane * 8);
        sts64(a + lane * 8, __float_as_uint(__uint_as_float(x0) + y0), __float_as_uint(__uint_as_float(x1) + y1));
        if (lane < 3) sts32(a + 512 + lane * 4, __float_as_uint(fmaf(c, df, __uint_as_float(lds32(a + 512 + lane * 4)))));
      }
    }
    __syncwarp();
    for (int n = 0; n < cnt; n++) {
      const uint32_t hv = hrow(nb + n); uint32_t x0, x1; lds64(x0, x1, ab + n * 528 + lane * 8);
      float y0 = 0.f, y1 = 0.f; rowmul(hv, (const uint32_t*)p.wh, y0, y1); rowmul(pack_bf16(__uint_as_float(x0), __uint_as_float(x1)), (const uint32_t*)p.wh + 64 * 32, y0, y1);
      const uint32_t o = badd(hv, pack_bf16(act(y0), act(y1)));
      p.out[(size_t)(nb + n) * 64 + 2 * lane] = (uint16_t)o; p.out[(size_t)(nb + n) * 64 + 2 * lane + 1] = (uint16_t)(o >> 16);
      if (lane < 3) p.out[(size_t)p.N * 64 + (size_t)(nb + n) * 3 + lane] = (uint16_t)pack_bf16(bf_lo(__ldg(p.pos + (size_t)(nb + n) * 3 + lane)) + __uint_as_float(lds32(ab + n * 528 + 512 + lane * 4)), 0.f);
    }
    __syncwarp();
  }
}

__global__ void __launch_bounds__(NT, 1) egnn_kernel(const __grid_constant__ Params p, const __grid_constant__ Maps maps) {
  extern __shared__ __align__(1024) unsigned char smraw[];
  const int tid = threadIdx.x, cta = blockIdx.x;
  const int e0 = cta * p.EPC, nb = max(0, min(p.EPC, p.E - e0)) * 4;
  STAMP(0);
  auto load_idx = [&](int c) {
    const int o = (c & 3) * CH, n = max(0, min(CH, nb - o));
    mbar_expect(BAR_C + c * 8, n);
    if (n) bulk_load(c < 4 ? a_dst(c) : A_SRC + o, (const char*)((c < 4 ? p.dst : p.src) + e0) + o, n, BAR_C + c * 8);
  };
  if (tid == 480 && !p.force_slow) {
#pragma unroll
    for (int c = 0; c < 4; c++) mbar_init(BAR_C + c * 8, 1);
    asm volatile("fence.mbarrier_init.release.cluster;" ::: "memory");
#pragma unroll
    for (int c = 0; c < 4; c++) load_idx(c);
  }
  if ((uint32_t)__cvta_generic_to_shared(smraw) != sb) return;
  if (p.force_slow) { slow_path(p); return; }
  uint32_t ep = ldg_poll(p.s->ep + cta * 32), tgb;
  const uint64_t tmb = (uint64_t)&maps;
  const int lane = tid & 31, wid = __shfl_sync(~0u, tid >> 5, 0), g8 = lane >> 2, q = lane & 3;
  uint32_t whx = 0;
  if (wid < 12) {
    if (tid < (A_CNT - A_MISC) / 16) sts128(A_MISC + tid * 16, 0, tid == 0 ? 16 : 0, 0, 0);
    const uint32_t acnt = A_CNT + ((tid + cta * p.NPC) & 511) * 4;
    sts32(acnt, A_TAB + tid * (CAP * 2));
    if (tid < 32) sts32(A_CNT + 2048 + tid * 4, A_TRASH);
    ep++; tgb = ep << 31;
    const uint32_t tga = (ep & 63) * 0x04000400u, tgh = tga & 0xFFFF0000u;
    {
      const uint32_t x = tga + (512 + (tid & 7) * 4) * 0x10001u;
#pragma unroll
      for (int k = 0; k < 3; k++) if (k < 2 || tid < (G + 1) * 8 - 2 * NX) {
        const uint32_t i = tid + k * NX, hw = ((i >> 3) & 31) - (i & 7) * 4;
        sts128(A_SA + i * 16, x, x + 0x10001u, x + 0x20002u, x + 0x30003u);
        sts32p(A_SA + i * 16 + hw * 4, tgh + (i & 7) * 16 + hw * 4 + 4, hw < 4);
      }
#pragma unroll
      for (int k = 0; k < 6; k++) if (k < 5 || tid < G * 16 - 5 * NX) sts128(A_SB + (tid + k * NX) * 16, tgb, tgb, tgb, tgb);
    }
    bar_sync(7, NT);
    STAMP(23);
  } else {
    if (wid == 15) asm volatile("ld.global.nc.u32 %0, [%1];" : "=r"(whx) : "l"((const uint32_t*)p.wh + (cta & 127) * 32 + lane));
    if (tid == 480 || tid == 448) {
#pragma unroll
      for (int c = 0; c < 10; c++) if (tid == 480 || c < 5) mbar_init(BAR_C + (tid == 480 ? 32 : 112) + c * 8, tid == 448 && c == 4 ? 16 : 1);
      asm volatile("fence.mbarrier_init.release.cluster;" ::: "memory");
    }
    if (tid - 416 < 7u) asm volatile("prefetch.tensormap [%0];" :: "l"(tmb + (tid - 416) * 128));
    __syncwarp();
    if (wid == 15) bar_arrive(7, NT); else bar_sync(7, NT);
    if (tid == 480) {
#pragma unroll 1
      for (int c = 4; c < 14; c++) {
        if (c >= WIN) mbar_wait(BAR_C + (c < 8 ? c - WIN : HW0) * 8, 0);
        if (c < 8) load_idx(c); else { mbar_expect(BAR_C + c * 8, 8192); tma_load(A_PT + (c - 8) * 8192, tmb + TM_H, cta * p.NPC + (c - 8) * 64, BAR_C + c * 8); }
      }
    }
    if (tid == 448) {
      mbar_expect(BAR_W, 2 * 8192 + 2048 + 256);
      tma_load(A_W, tmb + TM_WE, 64, BAR_W); tma_load(A_W + 8192, tmb + TM_WE, 0, BAR_W); tma_load(A_W3, tmb + TM_W3, 129, BAR_W);
      bulk_load(A_WD, p.we + 128 * 64, 128, BAR_W); bulk_load(A_WD + 128, p.wx, 128, BAR_W);
    }
    __syncwarp();
  }

  const int w = wid & 3;
  const uint32_t frag = (w * 16 + (lane & 15)) * 128 + (((lane >> 4) ^ (lane & 7)) << 4), pa = A_POSH + (w * 16 + g8) * 8 + q * 2;
  float a0[32], a1[32];
  float mx = 0.f;
  auto mma = [&](float (&acc)[32], int b, int blk) {
    const uint64_t da = DHI | ((A_PT + blk * 8192) >> 4), db = DHI | ((A_W + b * 8192) >> 4);
    wg_fence();
    ss64<0>(acc, da, db); ss64<1>(acc, da + 2, db + 128); ss64<1>(acc, da + 4, db + 256); ss64<1>(acc, da + 6, db + 384);
    wg_commit();
  };
  auto epi = [&](float (&acc)[32], int b, int blk) {
    uint32_t o[16];
#pragma unroll
    for (int j = 0; j < 16; j++) o[j] = pack_f16(acc[2 * j], acc[2 * j + 1]);
    if (b) {
#pragma unroll
      for (int j = 0; j < 32; j++) mx = fmaxf(mx, fabsf(acc[j]));
    } else {
#pragma unroll
      for (int r = 0; r < 2; r++) {
        const uint32_t T = __byte_perm(lds16(pa + blk * 512 + r * 64), 0, 0x4140);
#pragma unroll
        for (int j = 0; j < 4; j++) o[2 * j + r] &= 0xFFFCFFFCu;
        const uint32_t S = decode(o[r], o[2 + r], o[4 + r], o[6 + r]);
        const uint32_t X = (T - S) & 255, Y = XD ? S ^ T : X | ((T - ((S + X) & 0xFFFF0000u)) & 0x00FF0000u);
#pragma unroll
        for (int j = 0; j < 4; j++) o[2 * j + r] |= (Y >> (2 * j)) & 0x00030003u;
      }
    }
    const uint32_t a = (b ? A_PT : A_QS) + blk * 8192 + frag;
#pragma unroll
    for (int j = 0; j < 4; j++) stsm4(a ^ (j << 5), o[4 * j], o[4 * j + 1], o[4 * j + 2], o[4 * j + 3]);
  };
  uint32_t W3[16], PB[16], WX[8];
  auto frags = [&]() {
#pragma unroll
    for (int k = 0; k < 4; k++) ldsm4t(W3[4 * k], W3[4 * k + 1], W3[4 * k + 2], W3[4 * k + 3], A_W3 + (lane & 15) * 128 + ((((lane >> 4) + 2 * k) ^ (lane & 7)) << 4));
#pragma unroll
    for (int j = 0; j < 8; j++) WX[j] = lds32(A_WD + 128 + j * 16 + q * 4);
  };
  auto p_check = [&](int blk) {
    const uint32_t pm = __reduce_max_sync(~0u, __float_as_uint(mx));
    if (pm > 0x46000000u || (pm < 0x3A800000u && blk * 64 + (w + 1) * 16 <= min(p.NPC, p.N - cta * p.NPC))) sts32(A_MISC, 1);
  };
  if (wid >= 12) {
    const int node0 = cta * p.NPC, nloc = max(0, min(p.NPC, p.N - node0));
    if (w == 3) {
      const uint32_t mh = amax_warp(whx & 0x7FFF7FFFu);
      sts32(A_WHS + lane * 4, cta < 64 ? bhalf(whx) : mh && mh < 0x3B00 ? ~0u : b2h(bhalf(whx)));
      __syncwarp();
      if (lane == 0 && cta < 128) { proxy_fence(); asm volatile("cp.async.bulk.global.shared::cta.bulk_group [%0], [%1], 128;" :: "l"(p.s->wh + cta * 32), "r"(A_WHS) : "memory"); }
      __syncwarp();
      ep++;
    }
    else {
      const int t = tid - 384;
      uint32_t ps[12], mp = 0;
#pragma unroll
      for (int k = 0; k < 4; k++) {
        ps[3 * k] = ps[3 * k + 1] = ps[3 * k + 2] = 0;
        asm volatile("{.reg .pred p; setp.lt.s32 p, %4, %5;\n @p ld.global.nc.u16 %0, [%3];\n @p ld.global.nc.u16 %1, [%3+2];\n @p ld.global.nc.u16 %2, [%3+4];}"
          : "+r"(ps[3 * k]), "+r"(ps[3 * k + 1]), "+r"(ps[3 * k + 2]) : "l"(p.pos + (size_t)(node0 + t + 96 * k) * 3), "r"(t + 96 * k), "r"(p.N - node0));
      }
      mbar_wait(BAR_W, 0);
#pragma unroll
      for (int k = 0; k < 11; k++) if (k < 10 || w < 2) { uint32_t v[4]; const uint32_t a = A_W + (t + k * 96) * 16; lds128(v, a); sts128(a, bhalf(v[0]), bhalf(v[1]), bhalf(v[2]), bhalf(v[3])); }
      const uint32_t wd = lds32(A_WD + lane * 4), md = amax_warp(wd & 0x7FFF7FFFu);
      bool bad = md - 0x3B00 > 0x680;
      if (w < 2) {
        uint32_t mw = 0;
#pragma unroll
        for (int k = 0; k < 2; k++) { uint32_t v[4]; const uint32_t a = A_W3 + (t + k * 64) * 16; lds128(v, a);
          sts128(a, b2h(bhalf(v[0])), b2h(bhalf(v[1])), b2h(bhalf(v[2])), b2h(bhalf(v[3]))); mw = amax2(amax2(amax2(amax2(mw, v[0]), v[1]), v[2]), v[3]); }
        bad |= amax_warp(mw) - 0x3B00 > 0x680;
      } else {
#pragma unroll
        for (int r = 0; r < 8; r++) sts32(A_WD2 + r * 128 + ((lane * 4) ^ (r << 4)), (r & 1) ? 0 : r == 6 ? 0xF753F753u : b2h(bhalf(wd)));
        const uint32_t x = lds32(A_WD + 128 + lane * 4), ex = min(max(amax_warp(x & 0x7FFF7FFFu) >> 7, 20u), 230u);
        const float sc = __uint_as_float((252 - ex) << 23);
        sts32(A_WD + 128 + lane * 4, pack_f16(bf_lo(x) * sc, bf_hi(x) * sc)); sts32(A_MISC + 12, (ex + 2) << 23);
      }
#pragma unroll
      for (int k = 0; k < 4; k++) {
        const int n = t + 96 * k;
        sts64(A_POSH + n * 8, pack_f16(bf_lo(ps[3 * k]), bf_lo(ps[3 * k + 1])), pack_f16(bf_lo(ps[3 * k + 2]), 1.f));
        sts16(A_POSB + n * 6, ps[3 * k]); sts16(A_POSB + n * 6 + 2, ps[3 * k + 1]); sts16(A_POSB + n * 6 + 4, ps[3 * k + 2]);
        mp = amax2(amax2(mp, ps[3 * k] | (ps[3 * k + 1] << 16)), ps[3 * k + 2]);
      }
      mp = amax_warp(mp);
      if (bad || !(bf_lo(mp) * bf_lo(mp) * bf_lo(md) < 6000.f) || (mp < 0x3B80 && (w + 1) * 32 <= nloc)) sts32(A_MISC, 1);
      proxy_fence();
      if (w == 0) STAMP(16);
      bar_arrive(3, NX + 96);
      ep++;
    }
    bar_sync(6, 128);
#pragma unroll 1
    for (int blk = T3; blk < 6; blk = max(blk + 1, 4)) {
      mbar_wait(BAR_T + blk * 8, 0);
      if (w == 0 && blk == 5) STAMP(17);
      mma(a0, 0, blk); mma(a1, 1, blk);
      asm volatile("wgmma.wait_group.sync.aligned 1;" ::: "memory"); fence_regs(a0);
      epi(a0, 0, blk);
      wg_wait0(); fence_regs(a1);
      bar_sync(6, 128);
      if (w == 3 && blk == 5) {
        bar_sync(8, NX + 32);
        if (lane == 0) {
          proxy_fence();
#pragma unroll 1
          for (int b = 0; b * 64 < nloc; b++) tma_store(tmb + TM_Q, 0, node0 + b * 64, A_QS + b * 8192);
          STAMP(18);
        }
        __syncwarp();
      }
      epi(a1, 1, blk);
    }
    p_check(T3);
    frags();
    tgb = ep << 31;
  } else {
    const uint32_t acnt = A_CNT + ((tid + cta * p.NPC) & 511) * 4, tga = (ep & 63) * 0x04000400u, tgh = tga & 0xFFFF0000u;
    tgb = ep << 31;
    uint32_t d[16], oo[16], xx[16], lc[16], mxx = 0;
#pragma unroll
    for (int c = 0; c < 4; c++) {
      mbar_wait(BAR_C + c * 8, 0);
      if (c == 3) STAMP(1);
      lds128(d + 4 * c, a_dst(c) + tid * 16);
#pragma unroll
      for (int k = 4 * c; k < 4 * c + 4; k++) {
        if (tid * 16 + c * CH >= nb) d[k] = G * p.NPC;
        const uint32_t j = __umulhi(d[k], p.magic);
        xx[k] = atoms_add(A_SA + (j * 128 | ((j * 4) & 0x7C)), 258);
        oo[k] = j * 128;
      }
    }
#pragma unroll
    for (int k = 0; k < 16; k++) { oo[k] |= xx[k] & 0x7E; mxx = max(mxx, xx[k]); }
    if (mxx > tgh + 15900) {
#pragma unroll
      for (int k = 0; k < 16; k++) if (xx[k] > tgh + 15900) oo[k] = G * 128 + 64 + lane * 2;
    }
#pragma unroll
    for (int k = 0; k < 16; k++) sts16(A_SA + oo[k], (d[k] & 511) | tga);
    if (wid == 0) { bar_sync(1, NX); if (lane == 0) { proxy_fence(); tma_store(tmb + TM_XA, cta * 192, 0, A_SA); bulk_commit(); } __syncwarp(); } else bar_arrive(1, NX);
    STAMP(2);
    const uint32_t eb = tgb + ((tid * 4 + (cta & 3) * p.EPC) << 16);
#pragma unroll
    for (int c = 0; c < 4; c++) {
      mbar_wait(BAR_C + 32 + c * 8, 0);
      if (wid == 0 && c == 3) STAMP(21);
      lds128(lc + 4 * c, A_SRC + c * CH + tid * 16);
#pragma unroll
      for (int k = 4 * c; k < 4 * c + 4; k++) { lc[k] += eb + ((c * NX * 4 + (k & 3)) << 16); sts32(A_SB + oo[k] * 2, lc[k]); }
    }
    bar_sync(2, NX);
    if (tid == 0) { proxy_fence(); tma_store(tmb + TM_XB, cta * 96 + 32, 0, A_SB); bulk_commit(); p.s->ep[cta * 32] = ep; }
    __syncwarp();
    STAMP(3);
    if (mxx > tgh + 15900) {
#pragma unroll
      for (int k = 0; k < 16; k++) {
        const uint32_t j = __umulhi(d[k], p.magic), r = (xx[k] - tgh) / 258 - 62;
        if (r < 31 && j < G)
          asm volatile("st.relaxed.gpu.global.v2.u32 [%0], {%1, %2};" :: "l"(p.s->xe + (j * G + cta) * 32 + r), "r"(lc[k]), "r"((d[k] & 511) | (ep << 9)) : "memory");
      }
    }
    __syncwarp();
    constexpr int JS = 12; const int j0 = wid;
#pragma unroll
    for (int k = 0; k < 7; k++) if (k < 6 || tid < 385 * CAP / 8 + 9 - 6 * NX) sts128(A_TAB + (tid + k * NX) * 16, 0, 0, 0, 0);
    bar_sync(3, NX + 96);
    STAMP(12);
    const char* xin = (const char*)(p.s->x + cta * G * 24);
    uint32_t pk[11];
    const uint32_t rot = (lane + cta) & 31;
    auto poll_a = [&]() {
#pragma unroll
      for (int k = 0; k < 11; k++) pk[k] = ldg_poll(xin + (j0 + JS * k) * FS + rot * 4);
    };
    uint32_t xs = ~0u; uint2 xv;
    const uint32_t t0 = (wid >> 2) * BS + 128 + w * 256 + rot * 8, tx = lane ? tga : tgh;
    const uint32_t h1 = (cta & 31) * 4 + 4 + 62 * 258;
    int spin = 0;
    auto copy_b = [&]() {
      const uint32_t o = (j0 + JS * (lane >> 4)) * FS + 128 + (lane & 15) * 16, a = A_IN + ((wid >> 2) + 3 * (lane >> 4)) * BS + 128 + w * 256 + (lane & 15) * 16;
#pragma unroll
      for (int k = 0; k < 6; k++) if (k < 5 || lane < 16)
        asm volatile("cp.async.cg.shared.global.L2::cache_hint [%0], [%1], 16, %2;" :: "r"(a + k * 6 * BS), "l"(xin + o + k * 2 * JS * FS), "l"(pol_first()) : "memory");
    };
    {
      const int blk = (wid >> 2) + !T3;
      mbar_wait(BAR_T + blk * 8, 0);
      if (wid == 8) STAMP(22);
      mma(a0, 0, blk); if (!PL) mma(a1, 1, blk);
      asm volatile("wgmma.wait_group.sync.aligned %0;" :: "n"(!PL) : "memory"); fence_regs(a0);
      epi(a0, 0, blk);
      bar_arrive(8, NX + 32);
      poll_a();
      if (PL) mma(a1, 1, blk);
      wg_wait0(); fence_regs(a1);
      bar_sync(13 + (wid >> 2), 128);
      epi(a1, 1, blk);
      p_check(blk);
      if (FR == 0) frags();
      if (wid == 8) STAMP(24);
    }
    {
      {
        for (;;) {
          uint32_t mh = 0, bad = 0;
#pragma unroll
          for (int k = 0; k < 11; k++) { pk[k] ^= tx; mh = max(mh, pk[k]); bad |= pk[k]; }
          if (!__any_sync(~0u, bad & (lane ? 0xFC00FC00u : 0xFC000000u))) {
            if (__shfl_sync(~0u, mh, 0) > h1) {
              uint32_t base = 0;
#pragma unroll
              for (int k = 0; k < 11; k++) {
                const uint32_t c = (max(__shfl_sync(~0u, pk[k], 0), h1) - h1) / 258;
                if (lane - base < c) xs = (j0 + JS * k) * 32 + lane - base;
                base += c;
              }
              if (base > 31) { sts32(A_MISC, 1); xs = ~0u; }
              if (xs != ~0u) xv = ldg_poll2(p.s->xe + cta * G * 32 + xs);
              __syncwarp();
            }
            break;
          }
          if (++spin > 2000000) __trap();
          poll_a();
        }
        STAMP(14); if (wid == 8) STAMP(25);
        uint32_t r0[11], r1[11];
#pragma unroll
        for (int k = 0; k < 11; k++) {
          if (lane == 0) pk[k] = (512 + rot) * 0x10001u;
          r0[k] = atoms_add(A_CNT + (pk[k] & 0xFFFF) * 4, 2);
          r1[k] = atoms_add(A_CNT + (pk[k] >> 16) * 4, 2);
        }
#pragma unroll
        for (int k = 0; k < 11; k++) { sts16(min(r0[k], A_IN - 2), t0 + 3 * k * BS); sts16(min(r1[k], A_IN - 2), t0 + 3 * k * BS + 4); }
        if (wid == 8) STAMP(26);
      }
    }
    if (tid == 0) { asm volatile("cp.async.bulk.wait_group.read 0;" ::: "memory"); mbar_arrive(BAR_X); }
    __syncwarp();
    mbar_wait(BAR_X, 0);
    copy_b();
    STAMP(4);
    if (xs != ~0u) {
      for (int i = 0; (((xv.x ^ tgb) >> 31) | ((xv.y >> 9) ^ (ep & 0x7FFFFF))) && i < 2000000; i++) xv = ldg_poll2(p.s->xe + cta * G * 32 + xs);
      const uint32_t n = atoms_add(A_XC + (xs >> 7) * 4, 4), t = (xs >> 7) * BS + 4 + min(n, 120u);
      if (n > 120) sts32(A_MISC, 1);
      sts16(min(atoms_add(A_CNT + (xv.y & 511) * 4, 2), A_IN - 2), t);
      sts32(A_IN + t, xv.x);
    }
    __syncwarp();
    if (FR == 1) frags();
    bar_sync(4, NX);
    STAMP(5);
    {
      const uint32_t dg = (lds32(acnt) - (A_TAB + tid * (CAP * 2))) >> 1;
      const uint32_t dr = atoms_add(A_DH + min(dg, 63u) * 4, 1);
      bar_sync(5, NX);
      uint32_t hb, ha; lds64(hb, ha, A_DH + (62 - 2 * lane) * 4);
      uint32_t inc = ha + hb;
#pragma unroll
      for (int o = 1; o < 32; o <<= 1) { const uint32_t y = __shfl_up_sync(~0u, inc, o); if (lane >= o) inc += y; }
      const uint32_t idx = 63 - min(dg, 63u);
      const uint32_t e2 = __shfl_sync(~0u, (inc - hb) | ((inc - hb - ha) << 16), idx >> 1);
      const uint32_t pos = ((idx & 1) ? (e2 & 0xFFFF) : (e2 >> 16)) + dr;
      sts16(A_ROWS + pos * 2, tid);
      if (!(pos & 7)) sts32(A_LEN + (pos >> 1), max(1u, (dg + 1) >> 1));
      if (dg > CAP) sts32(A_MISC, 1);
    }
    STAMP(6);
    if (tid == 0) sts32(A_IN, 0xFFFF);
    for (;;) {
      asm volatile("cp.async.wait_all;" ::: "memory");
      __syncwarp();
      uint32_t bad = 0;
#pragma unroll
      for (int k = 0; k < 11; k++) { uint32_t x, y; lds64(x, y, A_IN + t0 + 3 * k * BS); bad |= (x ^ tgb) | (y ^ tgb); }
      if (!__any_sync(~0u, bad >> 31) || ++spin > 2000000) break;
      copy_b();
    }
    if (FR == 2) frags();
    STAMP(7);
  }
  if (wid == 15) {
    bar_arrive(11, NT);
    if (lane == 0) { bulk_commit(); asm volatile("cp.async.bulk.wait_group 0;" ::: "memory"); }
    __syncwarp();
    if (lane < NREP) asm volatile("red.relaxed.gpu.global.add.u32 [%0], 1;" :: "l"(p.s->cnt + lane * 32) : "memory");
    if (lane == 0) {
      STAMP(19);
      const uint32_t nbe = (p.E / G) & ~15u;
#pragma unroll 1
      for (int i = 0; i < PFA; i++)
        if (nbe) asm volatile("cp.async.bulk.prefetch.L2.global [%0], %1;" :: "l"((const char*)p.ea + (size_t)(i * G + cta) * nbe), "r"(nbe) : "memory");
      uint32_t c; int spin = 0;
      do asm volatile("ld.acquire.gpu.global.u32 %0, [%1];" : "=r"(c) : "l"(p.s->cnt + (cta % NREP) * 32) : "memory"); while ((int)(c - ep * G) < 0 && ++spin < 20000000);
      mbar_arrive(BAR_Q);
      STAMP(20);
    }
    __syncwarp();
  }
  uint32_t A2[4];
  const uint32_t ring = 4096 + wid * 4096, ering = (wid < 8 ? 69632 : A_E3 - 8 * 1536) + wid * 1536;
  const int oc = lane >> 3;
  const int r7 = lane & 7, ro = r7 >> 1, ri = 2 * (oc & 1) + (r7 & 1);
  uint64_t qp0 = (uint64_t)p.s->q + ((r7 ^ (2 * oc)) << 4), qp1 = qp0 ^ 16, epp = (uint64_t)p.ea + (((lane ^ oc) & 1) << 4) - (tgb >> 11);
  uint32_t dq = ring + oc * 512 + r7 * 16, de = ering + ((lane * 16) ^ ((oc >> 1) * 64));
  uint32_t rq = ring + (4 * ro + ri) * 128 + (((oc >> 1) ^ r7) << 4), re = ering + ro * 128 + ((ri ^ (2 * (ro >> 1))) << 5) + ((((oc >> 1) ^ ro) & 1) << 4);
  A2[0] = (g8 >> 1) == q ? ((g8 & 1) ? 0x3C000000u : 0x3C00u) : 0;
  A2[0] += lds32(A_MISC + 8); A2[1] = A2[0] + lds32(A_MISC + 8);
  asm volatile("" : "+l"(qp0), "+l"(qp1), "+l"(epp), "+r"(dq), "+r"(de), "+r"(rq), "+r"(re));
  bar_sync(wid < 15 ? 11 : 12, wid < 15 ? NT : 64);
  if (wid == 14) bar_arrive(12, 64);
  STAMP(13);
  if (__any_sync(~0u, lds32(A_MISC))) { sts32(A_MISC + 12, dq ^ de ^ rq ^ re ^ (uint32_t)qp0 ^ (uint32_t)qp1 ^ (uint32_t)(epp ^ (epp >> 32)) ^ A2[1]); __syncthreads(); slow_path(p); return; }

  uint32_t MS[8], acc[16], m[16], yh[8], A1[4], OP, TA, D = 0, U = 0, tt, tn, rec, rn, sl;
  re += lds32(A_MISC) + 1024 - ering; de += lds32(A_MISC) + 1024 - re; const uint32_t rtop = re + lds32(A_MISC);
  uint64_t pol;
  asm("createpolicy.range.global.L2::evict_normal.L2::evict_first.b64 %0, [%1], %2, %3;" : "=l"(pol) : "l"(p.ea), "r"(p.E * PFA), "r"(p.E * 32));
  const uint32_t eru = __reduce_max_sync(~0u, ering);
  const uint32_t zr = p.force_slow;
  uint32_t rk[4], ql1 = (uint32_t)qp1;
#pragma unroll
  for (int k = 0; k < 4; k++) rk[k] = (rq ^ (k * 32)) + lds32(A_MISC);
  uint32_t mk, ln, x1, x2, x3, x4, x5;
  auto lane_id = [&]() { uint32_t l; asm volatile("mov.u32 %0, %%laneid;" : "=r"(l)); return l; };
  auto nodes = [&](uint32_t r) {
    uint32_t t; asm volatile("mov.u32 %0, %%tid.x;" : "=r"(t));
    const uint32_t sc = p.sched[__shfl_sync(~0u, t >> 5, 0)];
    return lds16(A_ROWS + (sc & 63) * 16 + r * 2) | (lds16(A_ROWS + ((sc >> 6) & 63) * 16 + r * 2) << 10) | (lds16(A_ROWS + (sc >> 12) * 16 + r * 2) << 20);
  };
  auto lswitch = [&]() {
    TA = A_TAB + (x1 & 0xFFFF); x1 = __byte_perm(x1, 384 * CAP * 2, 0x5432);
    if (ln) mk |= 32u << (ln & 255);
    else {
      if (atoms_incp(A_MISC + 4, lane_id() == 0) == 31) {
        proxy_fence();
        mbar_expect(BAR_U, 16384);
#pragma unroll
        for (int k = 0; k < 2; k++)
          asm volatile("cp.async.bulk.tensor.2d.shared::cluster.global.mbarrier::complete_tx::bytes [%0], [%1, {0, %3}], [%2];" :: "r"(A_TAB + k * 8192), "l"(tmb + TM_WH), "r"(BAR_U), "r"(k * 64) : "memory");
      }
      __syncwarp();
    }
    ln >>= 8;
  };
  auto pload = [&](uint32_t a) {
#pragma unroll
    for (int k = 0; k < 4; k++) ldsm4t(PB[4 * k], PB[4 * k + 1], PB[4 * k + 2], PB[4 * k + 3], a ^ (k << 5));
  };
  auto flush = [&](int hf) {
    stsm4(((x4 & 0xFFFF) << 4) ^ (hf << 6), MS[4 * hf], MS[4 * hf + 1], MS[4 * hf + 2], MS[4 * hf + 3]);
    if (hf) { x3 = __byte_perm(x3, hadd(U, U >> 16), 0x5410); U = 0; x4 = __byte_perm(x4, 0, 0x1032); }
#pragma unroll
    for (int j = 4 * hf; j < 4 * hf + 4; j++) MS[j] = 0;
  };
  auto look1 = [&]() { asm volatile("ld.volatile.shared.u16 %0, [%1];" : "=r"(tn) : "r"(TA) : "memory"); asm volatile("add.u32 %0, %0, 4;" : "+r"(TA)); };
  auto look2 = [&](uint32_t tn) {
    asm volatile("ld.volatile.shared.u32 %0, [%1];" : "=r"(rn) : "r"(A_IN + tn) : "memory");
    tt = __umulhi(tn, 3728271u) * p.EPC4 + (rn >> 16); rn &= 0xFFFF;
    if (ABL & 1) tt = (tt & 0x1FFFF) + 65536;
  };
  auto issue_q = [&](uint32_t rec) {
#pragma unroll
    for (int i = 0; i < 4; i++)
      if (ABL & 2) asm volatile("{.reg .b64 a; .reg .pred p, l; setp.eq.u32 p, %2, 0xFFFF; setp.ge.u32 l, %3, 8; mad.wide.u32 a, %2, 128, %1;\n @l cp.async.cg.shared.global [%0], [a], 16, p;}"
        :: "r"(dq + i * 128), "l"((i & 1) ? (qp0 & ~0xFFFFFFFFull) | ql1 : qp0), "r"(__shfl_sync(~0u, rec, 2 * i, 8)), "r"(zr) : "memory");
      else asm volatile("{.reg .b64 a; .reg .pred p; setp.eq.u32 p, %2, 0xFFFF; mad.wide.u32 a, %2, 128, %1;\n cp.async.cg.shared.global [%0], [a], 16, p;}"
        :: "r"(dq + i * 128), "l"((i & 1) ? (qp0 & ~0xFFFFFFFFull) | ql1 : qp0), "r"(__shfl_sync(~0u, rec, 2 * i, 8)) : "memory");
    asm volatile("cp.async.commit_group;" ::: "memory");
    dq ^= 2048;
  };
  auto issue_e = [&](uint32_t a, uint32_t rn, uint32_t tt) {
    if (ABL & 2) asm volatile("{.reg .b64 a; .reg .pred p, l; setp.eq.u32 p, %3, 0xFFFF; setp.ge.u32 l, %5, 8; mad.wide.u32 a, %2, 32, %1;\n @l cp.async.cg.shared.global.L2::cache_hint [%0], [a], 16, p, %4;}"
      :: "r"(a), "l"(epp), "r"(tt), "r"(rn), "l"(pol), "r"(zr) : "memory");
    else asm volatile("{.reg .b64 a; .reg .pred p; setp.eq.u32 p, %3, 0xFFFF; mad.wide.u32 a, %2, 32, %1;\n cp.async.cg.shared.global.L2::cache_hint [%0], [a], 16, p, %4;}"
      :: "r"(a), "l"(epp), "r"(tt), "r"(rn), "l"(pol) : "memory");
  };
  auto act = [&](const uint32_t* y, int k) {
#pragma unroll
    for (int i = 0; i < 4; i++) { m[4 * k + i] = hsilu(y[i]); MS[2 * k + (i >> 1)] = hadd(MS[2 * k + (i >> 1)], m[4 * k + i]); }
  };
  auto cfin = [&](uint32_t d) {
    uint32_t c0_ = 0, c1_ = 0;
#pragma unroll
    for (int k = 0; k < 4; k++) { const int kk = (VAR & 32) ? k : k ^ 2; hmma(c0_, c1_, m + 4 * kk, WX[2 * kk], WX[2 * kk + 1]); }
    U = hfma(__byte_perm(c0_, c1_, 0x5410), d, U);
  };
  auto events = [&]() {
    if (mk & 1) flush(1);
    if (mk & 2) { flush(0); pload((x5 & 0xFFFF) << 4); x5 >>= 16; OP = __byte_perm(x3, 0, 0x1010); x3 >>= 16; }
    if (mk & 32) lswitch();
    if (mk < 16) {
      rec = x2 & 0xFFFF; x2 >>= 16;
      qp0 = (uint64_t)p.h + (qp0 & 127); ql1 = (uint32_t)qp0 ^ 16;
    }
  };
  auto step = [&](uint32_t st) {
    asm volatile("cp.async.wait_group 1;" ::: "memory");
    uint32_t E[4];
    ldsm4(E, re + eru);
#pragma unroll
    for (int k = 0; k < 4; k++) ldsm4(acc + 4 * k, rk[k] + st);
    look2(tn);
    issue_q(rec);
    issue_e(re + de, rn, tt); rec = rn;
    look1();
    re = __viaddmin_u32(re, -512, rtop);
    if (ABL & 4) { U ^= (E[0] ^ acc[0] ^ acc[4] ^ acc[8] ^ acc[12]) & zr; return; }
#pragma unroll
    for (int i = 0; i < 4; i++) A1[i] = pack_f16(__uint_as_float(__byte_perm(E[i], 0, 0x1044)), bf_hi(E[i]));
    const uint32_t Sa = decode(acc[0], acc[2], acc[4], acc[6]), Sb = decode(acc[1], acc[3], acc[5], acc[7]);
    const uint32_t Dp = D;
    D = hsub(OP, __byte_perm(Sa, Sb, 0x6420));
    const __half2 d = *(const __half2*)&D, x = __hmul2(d, d), y = __hmul2(__high2half2(d), __high2half2(d));
    A2[2] = *(const uint32_t*)&x; A2[3] = *(const uint32_t*)&y;
    if (VAR & 1) yh[4] |= A1[3] & zr;
    if (VAR & 2) yh[6] |= A2[3] & zr;
    act(yh, 2); act(yh + 4, 3);
#pragma unroll
    for (int j = 0; j < 8; j++) { hmma(acc[2 * j], acc[2 * j + 1], A1, W3[2 * j], W3[2 * j + 1]); hmma(acc[2 * j], acc[2 * j + 1], A2, PB[2 * j], PB[2 * j + 1]); }
    if (VAR & 4) m[(VAR & 32) ? 0 : 8] |= acc[0] & zr;
    cfin(Dp);
    if (VAR & 8) acc[6] |= acc[14] & zr;
    if (VAR & 16) acc[7] |= acc[10] & zr;
    if (VAR & 64) acc[5] |= acc[8] & zr;
    if (VAR & 128) acc[3] |= tt & zr;
    if (VAR & 256) acc[6] |= U & zr;
    if (VAR & 512) acc[2] |= m[15] & zr;
    if (VAR & 1024) acc[4] |= acc[12] & zr;
    act(acc, 0); act(acc + 4, 1);
#pragma unroll
    for (int i = 0; i < 8; i++) yh[i] = acc[8 + i];
  };
#pragma unroll
  for (int i = 0; i < 8; i++) { m[i] = 0; yh[i] = 0; MS[i] = 0; A1[i & 3] = 0; }
  { const uint32_t sc = p.sched[wid], g0 = sc & 63, g1 = (sc >> 6) & 63, g2 = sc >> 12;
    TA = A_TAB + lds16(A_ROWS + g0 * 16 + oc * 4 + (lane & 2)) * (CAP * 2) + ((lane >> 1) & 2);
    const uint32_t nd3 = nodes(r7);
    ln = __reduce_max_sync(~0u, lds32(A_LEN + g0 * 4) | (lds32(A_LEN + g1 * 4) << 8) | (lds32(A_LEN + g2 * 4) << 16));
    mk = 2u << max(ln & 255, 4u); ln >>= 8;
    uint32_t t3[3], ra, rb;
#pragma unroll
    for (int k = 0; k < 3; k++) { look1(); t3[k] = tn; }
    look1();
    look2(t3[0]); ra = rn; const uint32_t ta = tt;
    look2(t3[1]); rb = rn; const uint32_t tb = tt;
    look2(t3[2]);
    issue_e(re + de, ra, ta); issue_e(re + de - 512, rb, tb);
    mbar_wait(BAR_Q, 0);
    STAMP(8);
    issue_q(ra);
    auto prow = [&](int g) { const uint32_t nd = (nd3 >> (10 * g)) & 1023; return ((lane & 8) ? A_WD2 / 16 + r7 * 9 : A_PT / 16 + nd * 8 + (nd & 7)) ^ (lane >> 4); };
    auto mrow = [&](int g) { const uint32_t nd = (nd3 >> (10 * g)) & 1023; return A_PT / 16 + nd * 8 + (oc ^ (nd & 7)); };
    const uint32_t gn = __shfl_sync(~0u, nd3, g8);
    auto opos = [&](int g) { return lds16(A_POSH + ((gn >> (10 * g)) & 1023) * 8 + q * 2); };
    pload(prow(0) << 4); OP = opos(0) * 0x10001;
    issue_q(rb); issue_e(re + de - 1024, rn, tt); rec = rn;
    const uint32_t sn = __shfl_sync(~0u, nd3, 2 * oc + ((lane >> 1) & 1)), n0 = cta * p.NPC + ((sn >> ((lane & 4) ? 10 : 0)) & 1023), n1 = cta * p.NPC + (sn >> 20);
    x1 = (((sn >> 10) & 1023) | ((sn >> 20) << 16)) * (CAP * 2) + ((lane >> 1) & 2) * 0x10001;
    x3 = opos(1) | (opos(2) << 16); x4 = mrow(0) | (mrow(1) << 16); x5 = prow(1) | (prow(2) << 16);
    x2 = (n0 < p.N ? n0 : 0xFFFF) | ((n1 < p.N && !(lane & 4) ? n1 : 0xFFFF) << 16);
  }
  sl = 2048;
#pragma unroll 1
  do {
    if ((mk & 35) || mk < 16) events();
    sl ^= 2048; asm volatile("shr.u32 %0, %0, 1;" : "+r"(mk)); step(sl);
  } while (mk >= 4);
  sl += lds32(A_MISC); rq = rk[0] + lds32(A_MISC); dq = (dq + lds32(A_MISC)) & ~2048u;
  if (mk & 1) flush(1);
  STAMP(9);
  {
    int cta; asm volatile("mov.u32 %0, %%ctaid.x;" : "=r"(cta));
    const uint32_t l = lane_id(), node0 = cta * p.NPC; const int nloc = min(p.NPC, p.N - (int)node0);
    constexpr uint64_t dW = DHI | (A_TAB >> 4);
    float y1[32], y2[32];
    uint32_t H[16], po[3];
    asm volatile("cp.async.wait_group 1;" ::: "memory");
    __syncwarp();
    { const uint32_t a = (((l & 8) ? x4 >> 16 : x4 & 0xFFFF) ^ (l >> 3) ^ (l >> 4)) << 4;
#pragma unroll
      for (int k = 0; k < 4; k++) { ldsm4(acc + 4 * k, a ^ (k << 5)); ldsm4(H + 4 * k, (rq ^ (k * 32)) + (sl ^ 2048)); } }
    mbar_wait(BAR_U, 0);
    STAMP(10);
    wg_fence();
    rh64<0>(y1, acc, dW + 512); rh64<1>(y1, acc + 4, dW + 640); rh64<1>(y1, acc + 8, dW + 768); rh64<1>(y1, acc + 12, dW + 896);
    rs64<1>(y1, H, dW); rs64<1>(y1, H + 4, dW + 128); rs64<1>(y1, H + 8, dW + 256); rs64<1>(y1, H + 12, dW + 384);
    wg_commit();
    const uint32_t nd3 = nodes(l & 7);
    act(yh, 2); act(yh + 4, 3); cfin(D);
    { const uint32_t gn = __shfl_sync(~0u, nd3, l >> 2), a = A_POSH + (l & 3) * 2;
      sts16(a + (gn & 1023) * 8, x3); sts16(a + ((gn >> 10) & 1023) * 8, x3 >> 16); sts16(a + (gn >> 20) * 8, hadd(U, U >> 16)); }
    __syncwarp();
    if (l == 0) mbar_arrive(BAR_A);
    asm volatile("cp.async.wait_group 0;" ::: "memory");
    __syncwarp();
    wg_wait0(); fence_regs(y1);
#pragma unroll
    for (int k = 0; k < 4; k++) ldsm4(H + 4 * k, (rq ^ (k * 32)) + sl);
#pragma unroll
    for (int j = 0; j < 8; j++) acc[2 * j] = MS[j];
    wg_fence();
    rh64<0>(y2, acc, dW + 512); rh64<1>(y2, acc + 4, dW + 640); rh64<1>(y2, acc + 8, dW + 768); rh64<1>(y2, acc + 12, dW + 896);
    rs64<1>(y2, H, dW); rs64<1>(y2, H + 4, dW + 128); rs64<1>(y2, H + 8, dW + 256); rs64<1>(y2, H + 12, dW + 384);
    wg_commit();
    const float ov = y1[0] * y1[2];
    auto fin = [&](uint32_t x, float a, float b) { return badd(x, pack_bf16(silu(a), silu(b))); };
#pragma unroll
    for (int k = 0; k < 4; k += 2) {
      const uint32_t a = (rq ^ (k * 32)) + (sl ^ 2048); uint32_t x[8];
      ldsm4(x, a); ldsm4(x + 4, a ^ 32);
#pragma unroll
      for (int j = 0; j < 8; j++) x[j] = fin(x[j], y1[8 * k + 2 * j], y1[8 * k + 2 * j + 1]);
      stsm4(a, x[0], x[1], x[2], x[3]); stsm4(a ^ 32, x[4], x[5], x[6], x[7]);
    }
    { const uint32_t n0 = __shfl_sync(~0u, nd3, (l >> 2) & 6), n1 = __shfl_sync(~0u, nd3, ((l >> 2) & 6) | 1);
#pragma unroll
      for (int g = 0; g < 3; g++) po[g] = ((n0 >> (10 * g)) & 1023) | (((n1 >> (10 * g)) & 1023) << 16); }
    const uint64_t ob = (uint64_t)(p.out + (size_t)node0 * 64) + (((l & 7) ^ ((l >> 2) & 6)) << 4);
    auto put = [&](uint32_t a, uint32_t nn) {
      uint32_t v[8]; lds128(v, a); lds128(v + 4, a + 128);
#pragma unroll
      for (int i = 0; i < 2; i++)
        asm volatile("{.reg .pred p; .reg .b64 a; setp.lt.s32 p, %0, %1; mad.wide.u32 a, %0, 128, %2; @p st.global.v4.u32 [a], {%3,%4,%5,%6};}"
          :: "r"(i ? nn >> 16 : nn & 0xFFFF), "r"(nloc), "l"(ob ^ (i << 4)), "r"(v[4 * i]), "r"(v[4 * i + 1]), "r"(v[4 * i + 2]), "r"(v[4 * i + 3]) : "memory");
    };
    wg_wait0(); fence_regs(y2);
    __syncwarp();
    put(dq + (sl ^ 2048), po[0]); put(dq + 256 + (sl ^ 2048), po[1]);
    bool bad = !(fabsf(ov * y2[0] * 0.f) < 1.f);
#pragma unroll
    for (int j = 0; j < 16; j += 2) H[j] = fin(H[j], y2[2 * j], y2[2 * j + 1]);
#pragma unroll
    for (int k = 0; k < 4; k++) stsm4((rq ^ (k * 32)) + sl, H[4 * k], H[4 * k + 1], H[4 * k + 2], H[4 * k + 3]);
    __syncwarp();
    put(dq + sl, po[2]);
    const uint32_t c = __shfl_sync(~0u, atoms_incp(A_MISC + 8, l == 0), 0);
    if (c < 6) {
      mbar_wait(BAR_A, 0);
      uint32_t x[6];
#pragma unroll
      for (int k = 0; k < 6; k++) {
        const uint32_t i = c * 192 + k * 32 + l, u = lds16(A_POSH + i * 2 + i / 3 * 2);
        bad |= (u & 0x7C00) == 0x7C00;
        x[k] = pack_bf16(fmaf(__half2float(__ushort_as_half(u)), __uint_as_float(lds32(A_MISC + 12)), bf_lo(lds16(A_POSB + i * 2))), 0.f);
      }
      uint16_t* op = p.out + (size_t)p.N * 64 + (size_t)node0 * 3 + c * 192 + l;
#pragma unroll
      for (int k = 0; k < 6; k++)
        asm volatile("{.reg .pred p; setp.lt.s32 p, %0, %1; @p st.global.u16 [%2], %3;}" :: "r"(c * 192 + k * 32 + l), "r"(nloc * 3), "l"(op + k * 32), "h"((uint16_t)x[k]) : "memory");
    }
    if (__syncthreads_or(bad) && !ABL) { slow_path(p); return; }
  }
  STAMP(11);
}

}

typedef CUresult (*EncodeFn)(CUtensorMap*, CUtensorMapDataType, cuuint32_t, void*, const cuuint64_t*, const cuuint64_t*, const cuuint32_t*, const cuuint32_t*,
                             CUtensorMapInterleave, CUtensorMapSwizzle, CUtensorMapL2promotion, CUtensorMapFloatOOBfill);

extern "C" void kernel_launch(void* const* d_in, const int* in_sizes, int n_in, void* d_out, int out_size) {
  Params p; Maps maps;
  p.h = (const uint16_t*)d_in[0]; p.pos = (const uint16_t*)d_in[1]; p.ea = (const uint16_t*)d_in[2];
  p.src = (const int*)d_in[3]; p.dst = (const int*)d_in[4];
  p.we = (const uint16_t*)d_in[5]; p.wx = (const uint16_t*)d_in[6]; p.wh = (const uint16_t*)d_in[7];
  p.out = (uint16_t*)d_out;
  p.N = in_sizes[0] / 64; p.E = in_sizes[3];
  p.NPC = (p.N + G - 1) / G;
  p.EPC = ((p.E + G * 4 - 1) / (G * 4)) * 4;
  p.magic = (uint32_t)((1ull << 32) / (uint64_t)p.NPC) + 1;
  const uint32_t scheds[7][16] = {
    {0x28784, 0x2560a, 0x27548, 0x2b4c7, 0x2c2c9, 0x1f64c, 0x1b5d4, 0x22805, 0x2148d, 0x29742, 0x2fb80, 0x2d701, 0x2a406, 0x1a58f, 0x248c3, 0x2644e},
    {0x27787, 0x1f512, 0x25706, 0x2e741, 0x2fb40, 0x2938a, 0x2354d, 0x2a405, 0x2b802, 0x24883, 0x264c9, 0x1b60c, 0x2c584, 0x1a64b, 0x2144f, 0x285c8},
    {0x2e781, 0x258c3, 0x2b587, 0x247c6, 0x2148e, 0x20510, 0x2754f, 0x264cb, 0x2d602, 0x1d70d, 0x2fb00, 0x22645, 0x2a309, 0x1b68a, 0x285c4, 0x29448},
    {0x2758d, 0x26608, 0x2b5c6, 0x2d801, 0x2fb80, 0x1e513, 0x2a545, 0x1c64a, 0x2838c, 0x24883, 0x2544b, 0x293c7, 0x2c7c2, 0x1b490, 0x1d689, 0x23844},
    {0x2e543, 0x23608, 0x2c5c4, 0x26646, 0x2548e, 0x2a30a, 0x2858d, 0x2450b, 0x299c1, 0x2b7c2, 0x2fb40, 0x1b4d0, 0x21449, 0x22745, 0x20787, 0x1c68f},
    {0x299c2, 0x1d68d, 0x2a38a, 0x2f2c3, 0x2eb00, 0x2640c, 0x257c6, 0x28448, 0x22807, 0x2d841, 0x1c552, 0x2b504, 0x1e5d6, 0x234c9, 0x24645, 0x1b60f},
    {0x27449, 0x23786, 0x263cc, 0x29941, 0x2a604, 0x245cd, 0x2b7c3, 0x20510, 0x21747, 0x2c642, 0x2fb40, 0x1b68a, 0x2e2c5, 0x1c4d2, 0x28588, 0x2254e}};
  const uint32_t* sched = scheds[SCH];
  for (int i = 0; i < 16; i++) p.sched[i] = sched[i];
  p.EPC4 = p.EPC * 4;
  uint64_t al = (uint64_t)d_out;
  for (int i = 0; i < 8; i++) if (i != 1) al |= (uint64_t)d_in[i];
  p.force_slow = (al & 127) || (p.E & 3) || p.NPC > 384 || p.NPC < 2 || p.EPC > 6144;
  cudaGetSymbolAddress((void**)&p.s, g_s);
  void* fn = nullptr; cudaDriverEntryPointQueryResult qr;
  cudaGetDriverEntryPoint("cuTensorMapEncodeTiled", &fn, cudaEnableDefault, &qr);
  auto mk = [&](CUtensorMap* tm, void* base, int rows, int box) {
    const cuuint64_t dim[2] = {64, (cuuint64_t)rows}, str[1] = {128}; const cuuint32_t bx[2] = {64, (cuuint32_t)box}, es[2] = {1, 1};
    ((EncodeFn)fn)(tm, CU_TENSOR_MAP_DATA_TYPE_BFLOAT16, 2, base, dim, str, bx, es, CU_TENSOR_MAP_INTERLEAVE_NONE, CU_TENSOR_MAP_SWIZZLE_128B,
                   CU_TENSOR_MAP_L2_PROMOTION_NONE, CU_TENSOR_MAP_FLOAT_OOB_FILL_NONE);
  };
  mk(&maps.m[TM_H / 128], d_in[0], p.N, 64); mk(&maps.m[TM_WE / 128], d_in[5], 145, 64); mk(&maps.m[TM_WH / 128], p.s->wh, 128, 64);
  mk(&maps.m[TM_Q / 128], p.s->q, p.N, 64);
  mk(&maps.m[TM_W3 / 128], d_in[5], 145, 16);
  for (int k = 0; k < 2; k++) {
    const cuuint64_t dim[2] = {(cuuint64_t)G * (192 >> k), (cuuint64_t)G}, str[1] = {(cuuint64_t)G * FS}; const cuuint32_t bx[2] = {64, G}, es[2] = {1, 1};
    ((EncodeFn)fn)(&maps.m[TM_XA / 128 + k], k ? CU_TENSOR_MAP_DATA_TYPE_UINT32 : CU_TENSOR_MAP_DATA_TYPE_UINT16, 2, p.s->x, dim, str, bx, es, CU_TENSOR_MAP_INTERLEAVE_NONE,
                   CU_TENSOR_MAP_SWIZZLE_NONE, CU_TENSOR_MAP_L2_PROMOTION_NONE, CU_TENSOR_MAP_FLOAT_OOB_FILL_NONE);
  }
  cudaFuncSetAttribute(egnn_kernel, cudaFuncAttributeMaxDynamicSharedMemorySize, SMEM);
  egnn_kernel<<<G, NT, SMEM>>>(p, maps);
}
```

```cpp
#include <cuda_runtime.h>
#include <cuda_bf16.h>
#include <cuda_fp16.h>
#include <cuda.h>
#include <stdint.h>

#define PFA 6
#define WIN 6
namespace {

constexpr int G = 132;
constexpr int NT = 512;
constexpr int CAP = 48;
constexpr int FS = 384;
constexpr int BS = 1152;
constexpr uint32_t sb = 1024;

constexpr uint32_t A_RING = sb;
constexpr uint32_t A_PT = A_RING + 16 * 5120;
constexpr uint32_t A_W3 = A_PT + 49152;
constexpr uint32_t A_TAB = A_W3 + 2048;
constexpr uint32_t A_IN = A_TAB + 37888;
constexpr uint32_t A_WD = A_IN + G * FS + 512;
constexpr uint32_t A_WD2 = A_WD + 256;
constexpr uint32_t A_BAR = A_WD2 + 1024;
constexpr uint32_t A_MISC = A_BAR + 160;
constexpr uint32_t A_DH = A_MISC + 16;
constexpr uint32_t A_CNT = A_DH + 256;
constexpr uint32_t A_POSH = A_CNT + 2176;
constexpr uint32_t A_POSB = A_POSH + 3072;
constexpr uint32_t A_ROWS = A_POSB + 2304;
constexpr uint32_t A_LEN = A_ROWS + 768;
constexpr uint32_t A_END = A_LEN + 192;
constexpr uint32_t A_XC = A_TAB + 385 * CAP * 2, A_TRASH = A_XC + 144;
constexpr uint32_t A_E3 = A_IN + G / 4 * BS;
constexpr uint32_t A_WHS = A_PT - 128;
constexpr int SMEM = A_END - sb;
static_assert(SMEM <= 232448 && A_TAB % 1024 == 0 && A_IN % 1024 == 0 && A_PT % 1024 == 0 && A_WD2 % 128 == 0 && A_ROWS % 16 == 0, "smem");
constexpr int NX = 384, CH = NX * 16;
constexpr uint32_t A_QS = A_RING, A_W = A_QS + 49152, A_SA = A_IN, A_SB = A_SA + (G + 1) * 128, A_SRC = A_TAB;
__host__ __device__ constexpr uint32_t a_dst(int k) { return k < 2 ? A_W + 16384 + k * CH : A_SRC + (k + 2) * CH; }
static_assert(a_dst(1) + CH <= A_PT && a_dst(3) + CH <= A_IN && A_SB + (G + 1) * 256 <= A_WD, "staging");
constexpr uint32_t BAR_C = A_BAR, BAR_T = BAR_C + 64, BAR_W = A_BAR + 112, BAR_U = A_BAR + 120, BAR_Q = A_BAR + 128, BAR_X = A_BAR + 136, BAR_A = A_BAR + 144;

#define ABL 0
#define VAR 608
#define HW0 4
constexpr int NREP = 8;
struct Scratch {
  uint4 q[(G * 384 + 64) * 8];
  uint4 x[G * G * 24];
  uint2 xe[G * G * 32];
  uint32_t wh[128 * 32];
  uint32_t ep[G * 32];
  uint32_t cnt[NREP * 32];
};
__device__ __align__(256) Scratch g_s;
#define STAMP(k)

struct Maps { CUtensorMap m[7]; };
constexpr int TM_H = 0, TM_WE = 128, TM_WH = 256, TM_Q = 384, TM_XA = 512, TM_XB = 640, TM_W3 = 768;
struct Params {
  const int* dst; const int* src; int E, EPC, force_slow, NPC; Scratch* s; int N; uint32_t magic;
  const uint16_t* h; const uint16_t* pos; const uint16_t* ea; const uint16_t* we; const uint16_t* wx; const uint16_t* wh; uint16_t* out;
  uint32_t EPC4, sched[16];
};

#define R32(d) "+f"(d[0]),"+f"(d[1]),"+f"(d[2]),"+f"(d[3]),"+f"(d[4]),"+f"(d[5]),"+f"(d[6]),"+f"(d[7]),"+f"(d[8]),"+f"(d[9]),"+f"(d[10]),"+f"(d[11]),"+f"(d[12]),"+f"(d[13]),"+f"(d[14]),"+f"(d[15]),"+f"(d[16]),"+f"(d[17]),"+f"(d[18]),"+f"(d[19]),"+f"(d[20]),"+f"(d[21]),"+f"(d[22]),"+f"(d[23]),"+f"(d[24]),"+f"(d[25]),"+f"(d[26]),"+f"(d[27]),"+f"(d[28]),"+f"(d[29]),"+f"(d[30]),"+f"(d[31])
#define S32 "{%0,%1,%2,%3,%4,%5,%6,%7,%8,%9,%10,%11,%12,%13,%14,%15,%16,%17,%18,%19,%20,%21,%22,%23,%24,%25,%26,%27,%28,%29,%30,%31}"
#define DI __device__ __forceinline__

constexpr uint64_t DHI = (64ull << 32) | (1ull << 62);
template<int SD> DI void ss64(float (&d)[32], uint64_t da, uint64_t db) {
  asm volatile("wgmma.mma_async.sync.aligned.m64n64k16.f32.bf16.bf16 " S32 ", %32, %33, %34, 1, 1, 0, 1;" : R32(d) : "l"(da), "l"(db), "n"(SD)); }
template<int SD> DI void rs64(float (&d)[32], const uint32_t* a, uint64_t db) {
  asm volatile("wgmma.mma_async.sync.aligned.m64n64k16.f32.bf16.bf16 " S32 ", {%32,%33,%34,%35}, %36, %37, 1, 1, 1;" : R32(d) : "r"(a[0]), "r"(a[1]), "r"(a[2]), "r"(a[3]), "l"(db), "n"(SD)); }
template<int SD> DI void rh64(float (&d)[32], const uint32_t* a, uint64_t db) {
  asm volatile("wgmma.mma_async.sync.aligned.m64n64k16.f32.f16.f16 " S32 ", {%32,%33,%34,%35}, %36, %37, 1, 1, 1;" : R32(d) : "r"(a[0]), "r"(a[1]), "r"(a[2]), "r"(a[3]), "l"(db), "n"(SD)); }
DI void wg_fence() { asm volatile("wgmma.fence.sync.aligned;" ::: "memory"); }
DI void wg_commit() { asm volatile("wgmma.commit_group.sync.aligned;" ::: "memory"); }
DI void wg_wait0() { asm volatile("wgmma.wait_group.sync.aligned 0;" ::: "memory"); }
DI void fence_regs(float (&d)[32]) { asm volatile("" : R32(d) :: "memory"); }
DI void proxy_fence() { asm volatile("fence.proxy.async.shared::cta;" ::: "memory"); }
DI void hmma(uint32_t& d0, uint32_t& d1, const uint32_t* a, uint32_t b0, uint32_t b1) {
  asm("mma.sync.aligned.m16n8k16.row.col.f16.f16.f16.f16 {%0,%1}, {%2,%3,%4,%5}, {%6,%7}, {%0,%1};" : "+r"(d0), "+r"(d1) : "r"(a[0]), "r"(a[1]), "r"(a[2]), "r"(a[3]), "r"(b0), "r"(b1)); }
DI uint64_t pol_first() { uint64_t r; asm("createpolicy.fractional.L2::evict_first.b64 %0, 1.0;" : "=l"(r)); return r; }
DI float tanh_ap(float x) { float y; asm("tanh.approx.f32 %0, %1;" : "=f"(y) : "f"(x)); return y; }
DI float silu(float y) { return fmaf(y, tanh_ap(y), y); }
DI uint32_t pack_bf16(float lo, float hi) { uint32_t r; asm("cvt.rn.bf16x2.f32 %0, %1, %2;" : "=r"(r) : "f"(hi), "f"(lo)); return r; }
DI uint32_t pack_f16(float lo, float hi) { uint32_t r; asm("cvt.rn.f16x2.f32 %0, %1, %2;" : "=r"(r) : "f"(hi), "f"(lo)); return r; }
DI float bf_lo(uint32_t v) { return __uint_as_float(v << 16); }
DI float bf_hi(uint32_t v) { return __uint_as_float(v & 0xFFFF0000u); }
DI uint32_t b2h(uint32_t v) { return pack_f16(bf_lo(v), bf_hi(v)); }
DI uint32_t hadd(uint32_t a, uint32_t b) { uint32_t r; asm("add.rn.f16x2 %0, %1, %2;" : "=r"(r) : "r"(a), "r"(b)); return r; }
DI uint32_t hsub(uint32_t a, uint32_t b) { uint32_t r; asm("sub.rn.f16x2 %0, %1, %2;" : "=r"(r) : "r"(a), "r"(b)); return r; }
DI uint32_t hfma(uint32_t a, uint32_t b, uint32_t c) { uint32_t r; asm("fma.rn.f16x2 %0, %1, %2, %3;" : "=r"(r) : "r"(a), "r"(b), "r"(c)); return r; }
DI uint32_t hsilu(uint32_t y) { uint32_t t; asm("tanh.approx.f16x2 %0, %1;" : "=r"(t) : "r"(y)); return hfma(y, t, y); }
DI uint32_t badd(uint32_t a, uint32_t b) { uint32_t r; asm("add.rn.bf16x2 %0, %1, %2;" : "=r"(r) : "r"(a), "r"(b)); return r; }
DI uint32_t bhalf(uint32_t v) { uint32_t r; asm("mul.rn.bf16x2 %0, %1, %2;" : "=r"(r) : "r"(v), "r"(0x3F003F00u)); return r; }
DI uint32_t amax2(uint32_t mx, uint32_t v) { return __vmaxu2(mx, v & 0x7FFF7FFFu); }
DI uint32_t amax_warp(uint32_t mx) { return __reduce_max_sync(~0u, max(mx & 0xFFFF, mx >> 16)); }
DI uint32_t decode(uint32_t a, uint32_t b, uint32_t c, uint32_t d) {
  return a + b * 4 + c * 16 + d * 64;
}
DI void mbar_wait(uint32_t bar, uint32_t parity) {
  asm volatile("{.reg .pred p; .reg .u32 c; mov.u32 c, 0;\n"
    "LW_%=: mbarrier.try_wait.parity.shared::cta.b64 p, [%0], %1;\n"
    "@p bra.uni LD_%=;\n add.u32 c, c, 1; setp.lt.u32 p, c, 20000000;\n @p bra.uni LW_%=;\n LD_%=:}" :: "r"(bar), "r"(parity) : "memory");
}
DI void mbar_arrive(uint32_t bar) { asm volatile("mbarrier.arrive.shared::cta.b64 _, [%0];" :: "r"(bar) : "memory"); }
DI void bar_sync(int id, int n) { asm volatile("bar.sync %0, %1;" :: "r"(id), "r"(n) : "memory"); }
DI void bar_arrive(int id, int n) { asm volatile("bar.arrive %0, %1;" :: "r"(id), "r"(n) : "memory"); }
DI void sts128(uint32_t a, uint32_t x, uint32_t y, uint32_t z, uint32_t w) { asm volatile("st.shared.v4.u32 [%0], {%1,%2,%3,%4};" :: "r"(a), "r"(x), "r"(y), "r"(z), "r"(w) : "memory"); }
DI void sts64(uint32_t a, uint32_t x, uint32_t y) { asm volatile("st.shared.v2.u32 [%0], {%1,%2};" :: "r"(a), "r"(x), "r"(y) : "memory"); }
DI void sts32(uint32_t a, uint32_t x) { asm volatile("st.shared.u32 [%0], %1;" :: "r"(a), "r"(x) : "memory"); }
DI void sts16(uint32_t a, uint32_t x) { asm volatile("st.shared.u16 [%0], %1;" :: "r"(a), "h"((uint16_t)x) : "memory"); }
DI void sts32p(uint32_t a, uint32_t x, bool p) { asm volatile("{.reg .pred p; setp.ne.b32 p, %2, 0; @p st.shared.u32 [%0], %1;}" :: "r"(a), "r"(x), "r"((int)p) : "memory"); }
DI void lds128(uint32_t* v, uint32_t a) { asm volatile("ld.shared.v4.u32 {%0, %1, %2, %3}, [%4];" : "=r"(v[0]), "=r"(v[1]), "=r"(v[2]), "=r"(v[3]) : "r"(a) : "memory"); }
DI void lds64(uint32_t& x, uint32_t& y, uint32_t a) { asm volatile("ld.shared.v2.u32 {%0, %1}, [%2];" : "=r"(x), "=r"(y) : "r"(a) : "memory"); }
DI uint32_t lds32(uint32_t a) { uint32_t x; asm volatile("ld.shared.u32 %0, [%1];" : "=r"(x) : "r"(a) : "memory"); return x; }
DI uint32_t lds16(uint32_t a) { uint32_t x; asm volatile("ld.shared.u16 %0, [%1];" : "=r"(x) : "r"(a) : "memory"); return x; }
DI uint32_t atoms_add(uint32_t a, uint32_t v) { uint32_t r; asm volatile("atom.shared.add.u32 %0, [%1], %2;" : "=r"(r) : "r"(a), "r"(v) : "memory"); return r; }
DI uint32_t atoms_incp(uint32_t a, bool p) { uint32_t r = 0; asm volatile("{.reg .pred p; setp.ne.b32 p, %2, 0; @p atom.shared.add.u32 %0, [%1], 1;}" : "+r"(r) : "r"(a), "r"((int)p) : "memory"); return r; }
DI uint32_t ldg_poll(const void* a) { uint32_t x; asm volatile("ld.relaxed.gpu.global.u32 %0, [%1];" : "=r"(x) : "l"(a) : "memory"); return x; }
DI uint2 ldg_poll2(const void* a) { uint2 x; asm volatile("ld.relaxed.gpu.global.v2.u32 {%0, %1}, [%2];" : "=r"(x.x), "=r"(x.y) : "l"(a) : "memory"); return x; }
DI void bulk_load(uint32_t dst, const void* src, uint32_t bytes, uint32_t bar) {
  asm volatile("cp.async.bulk.shared::cluster.global.mbarrier::complete_tx::bytes.L2::cache_hint [%0], [%1], %2, [%3], %4;" :: "r"(dst), "l"(src), "r"(bytes), "r"(bar), "l"(pol_first()) : "memory"); }
DI void mbar_expect(uint32_t bar, uint32_t bytes) { asm volatile("mbarrier.arrive.expect_tx.shared::cta.b64 _, [%0], %1;" :: "r"(bar), "r"(bytes) : "memory"); }
DI void mbar_init(uint32_t bar, int n) { asm volatile("mbarrier.init.shared::cta.b64 [%0], %1;" :: "r"(bar), "r"(n) : "memory"); }
DI void tma_load(uint32_t dst, uint64_t tm, int row, uint32_t bar) {
  asm volatile("cp.async.bulk.tensor.2d.shared::cluster.global.mbarrier::complete_tx::bytes.L2::cache_hint [%0], [%1, {%3, %4}], [%2], %5;" :: "r"(dst), "l"(tm), "r"(bar), "r"(0), "r"(row), "l"(pol_first()) : "memory"); }
DI void tma_store(uint64_t tm, int col, int row, uint32_t src) {
  asm volatile("cp.async.bulk.tensor.2d.global.shared::cta.bulk_group [%0, {%2, %3}], [%1];" :: "l"(tm), "r"(src), "r"(col), "r"(row) : "memory"); }
DI void bulk_commit() { asm volatile("cp.async.bulk.commit_group;" ::: "memory"); }
DI void stsm4(uint32_t a, uint32_t x, uint32_t y, uint32_t z, uint32_t w) { asm volatile("stmatrix.sync.aligned.m8n8.x4.shared.b16 [%0], {%1,%2,%3,%4};" :: "r"(a), "r"(x), "r"(y), "r"(z), "r"(w) : "memory"); }
DI void ldsm4(uint32_t* v, uint32_t a) { asm volatile("ldmatrix.sync.aligned.m8n8.x4.shared.b16 {%0,%1,%2,%3}, [%4];" : "=r"(v[0]), "=r"(v[1]), "=r"(v[2]), "=r"(v[3]) : "r"(a) : "memory"); }
DI void ldsm4t(uint32_t& x, uint32_t& y, uint32_t& z, uint32_t& w, uint32_t a) { asm volatile("ldmatrix.sync.aligned.m8n8.x4.trans.shared.b16 {%0,%1,%2,%3}, [%4];" : "=r"(x), "=r"(y), "=r"(z), "=r"(w) : "r"(a) : "memory"); }

__device__ __noinline__ void slow_path(const Params& p) {
  const int lane = threadIdx.x & 31, wid = threadIdx.x >> 5;
  const uint32_t ab = sb + wid * (24 * 528);
  const uint32_t* we = (const uint32_t*)p.we;
  const int nend = min(p.N, (blockIdx.x + 1) * p.NPC);
  auto rowmul = [&](uint32_t hv, const uint32_t* w, float& y0, float& y1) {
#pragma unroll 4
    for (int k = 0; k < 32; k++) {
      const uint32_t hk = __shfl_sync(~0u, hv, k), wa = __ldg(w + 2 * k * 32 + lane), wb = __ldg(w + (2 * k + 1) * 32 + lane);
      y0 = fmaf(bf_lo(hk), bf_lo(wa), fmaf(bf_hi(hk), bf_lo(wb), y0)); y1 = fmaf(bf_lo(hk), bf_hi(wa), fmaf(bf_hi(hk), bf_hi(wb), y1));
    }
  };
  auto act = [](float x) { return x / (1.f + __expf(-x)); };
  auto hrow = [&](int n) { return __ldg(p.h + (size_t)n * 64 + 2 * lane) | ((uint32_t)__ldg(p.h + (size_t)n * 64 + 2 * lane + 1) << 16); };
  const uint32_t wdv = __ldg(we + 128 * 32 + lane), wxv = __ldg((const uint32_t*)p.wx + lane);
  for (int nb = blockIdx.x * p.NPC + wid * 24; nb < nend; nb += 384) {
    const int cnt = min(24, nend - nb);
    for (int n = 0; n < cnt; n++) {
      float y0 = 0.f, y1 = 0.f; rowmul(hrow(nb + n), we, y0, y1);
      sts64(ab + n * 528 + lane * 8, 0, 0); sts64(ab + n * 528 + 256 + lane * 8, __float_as_uint(y0), __float_as_uint(y1));
      if (lane < 4) sts32(ab + n * 528 + 512 + lane * 4, 0);
    }
    __syncwarp();
    for (int base = 0; base < p.E; base += 32) {
      const uint32_t dl = base + lane < p.E ? (uint32_t)(__ldg(p.dst + base + lane) - nb) : 0xFFFFFFFFu;
      uint32_t mk = __ballot_sync(~0u, dl < (uint32_t)cnt);
      while (mk) {
        const int l = __ffs(mk) - 1; mk &= mk - 1;
        const int e = base + l, n = __shfl_sync(~0u, dl, l), s = __ldg(p.src + e);
        const uint32_t a = ab + n * 528;
        float df = 0.f;
        if (lane < 3) df = bf_lo(pack_bf16(bf_lo(__ldg(p.pos + (size_t)(nb + n) * 3 + lane)) - bf_lo(__ldg(p.pos + (size_t)s * 3 + lane)), 0.f));
        float d2 = df * df; d2 += __shfl_xor_sync(~0u, d2, 1); d2 += __shfl_xor_sync(~0u, d2, 2); d2 = __shfl_sync(~0u, d2, 0);
        uint32_t x0, x1; lds64(x0, x1, a + 256 + lane * 8);
        float y0 = fmaf(d2, bf_lo(wdv), __uint_as_float(x0)), y1 = fmaf(d2, bf_hi(wdv), __uint_as_float(x1));
        rowmul(hrow(s), we + 64 * 32, y0, y1);
        for (int k = 0; k < 16; k++) { const float ev = bf_lo(__ldg(p.ea + (size_t)e * 16 + k)); const uint32_t w = __ldg(we + (129 + k) * 32 + lane); y0 = fmaf(ev, bf_lo(w), y0); y1 = fmaf(ev, bf_hi(w), y1); }
        y0 = act(y0); y1 = act(y1);
        float c = y0 * bf_lo(wxv) + y1 * bf_hi(wxv);
#pragma unroll
        for (int o = 16; o; o >>= 1) c += __shfl_xor_sync(~0u, c, o);
        lds64(x0, x1, a + lane * 8);
        sts64(a + lane * 8, __float_as_uint(__uint_as_float(x0) + y0), __float_as_uint(__uint_as_float(x1) + y1));
        if (lane < 3) sts32(a + 512 + lane * 4, __float_as_uint(fmaf(c, df, __uint_as_float(lds32(a + 512 + lane * 4)))));
      }
    }
    __syncwarp();
    for (int n = 0; n < cnt; n++) {
      const uint32_t hv = hrow(nb + n); uint32_t x0, x1; lds64(x0, x1, ab + n * 528 + lane * 8);
      float y0 = 0.f, y1 = 0.f; rowmul(hv, (const uint32_t*)p.wh, y0, y1); rowmul(pack_bf16(__uint_as_float(x0), __uint_as_float(x1)), (const uint32_t*)p.wh + 64 * 32, y0, y1);
      const uint32_t o = badd(hv, pack_bf16(act(y0), act(y1)));
      p.out[(size_t)(nb + n) * 64 + 2 * lane] = (uint16_t)o; p.out[(size_t)(nb + n) * 64 + 2 * lane + 1] = (uint16_t)(o >> 16);
      if (lane < 3) p.out[(size_t)p.N * 64 + (size_t)(nb + n) * 3 + lane] = (uint16_t)pack_bf16(bf_lo(__ldg(p.pos + (size_t)(nb + n) * 3 + lane)) + __uint_as_float(lds32(ab + n * 528 + 512 + lane * 4)), 0.f);
    }
    __syncwarp();
  }
}

__global__ void __launch_bounds__(NT, 1) egnn_kernel(const __grid_constant__ Params p, const __grid_constant__ Maps maps) {
  extern __shared__ __align__(1024) unsigned char smraw[];
  const int tid = threadIdx.x, cta = blockIdx.x;
  const int e0 = cta * p.EPC, nb = max(0, min(p.EPC, p.E - e0)) * 4;
  STAMP(0);
  auto load_idx = [&](int c) {
    const int o = (c & 3) * CH, n = max(0, min(CH, nb - o));
    mbar_expect(BAR_C + c * 8, n);
    if (n) bulk_load(c < 4 ? a_dst(c) : A_SRC + o, (const char*)((c < 4 ? p.dst : p.src) + e0) + o, n, BAR_C + c * 8);
  };
  if (tid == 480 && !p.force_slow) {
#pragma unroll
    for (int c = 0; c < 4; c++) mbar_init(BAR_C + c * 8, 1);
    asm volatile("fence.mbarrier_init.release.cluster;" ::: "memory");
#pragma unroll
    for (int c = 0; c < 4; c++) load_idx(c);
  }
  if ((uint32_t)__cvta_generic_to_shared(smraw) != sb) return;
  if (p.force_slow) { slow_path(p); return; }
  uint32_t ep = ldg_poll(p.s->ep + cta * 32), tgb;
  const uint64_t tmb = (uint64_t)&maps;
  const int lane = tid & 31, wid = __shfl_sync(~0u, tid >> 5, 0), g8 = lane >> 2, q = lane & 3;
  uint32_t whx = 0;
  if (wid < 12) {
    if (tid < (A_CNT - A_MISC) / 16) sts128(A_MISC + tid * 16, 0, tid == 0 ? 16 : 0, 0, 0);
    const uint32_t acnt = A_CNT + ((tid + cta * p.NPC) & 511) * 4;
    sts32(acnt, A_TAB + tid * (CAP * 2));
    if (tid < 32) sts32(A_CNT + 2048 + tid * 4, A_TRASH);
    ep++; tgb = ep << 31;
    const uint32_t tga = (ep & 63) * 0x04000400u, tgh = tga & 0xFFFF0000u;
    {
      const uint32_t x = tga + (512 + (tid & 7) * 4) * 0x10001u;
#pragma unroll
      for (int k = 0; k < 3; k++) if (k < 2 || tid < (G + 1) * 8 - 2 * NX) {
        const uint32_t i = tid + k * NX, hw = ((i >> 3) & 31) - (i & 7) * 4;
        sts128(A_SA + i * 16, x, x + 0x10001u, x + 0x20002u, x + 0x30003u);
        sts32p(A_SA + i * 16 + hw * 4, tgh + (i & 7) * 16 + hw * 4 + 4, hw < 4);
      }
#pragma unroll
      for (int k = 0; k < 6; k++) if (k < 5 || tid < G * 16 - 5 * NX) sts128(A_SB + (tid + k * NX) * 16, tgb, tgb, tgb, tgb);
    }
    bar_sync(7, NT);
    STAMP(23);
  } else {
    if (wid == 15) asm volatile("ld.global.nc.u32 %0, [%1];" : "=r"(whx) : "l"((const uint32_t*)p.wh + (cta & 127) * 32 + lane));
    if (tid == 480 || tid == 448) {
#pragma unroll
      for (int c = 0; c < 10; c++) if (tid == 480 || c < 5) mbar_init(BAR_C + (tid == 480 ? 32 : 112) + c * 8, tid == 448 && c == 4 ? 16 : 1);
      asm volatile("fence.mbarrier_init.release.cluster;" ::: "memory");
    }
    if (tid - 416 < 7u) asm volatile("prefetch.tensormap [%0];" :: "l"(tmb + (tid - 416) * 128));
    __syncwarp();
    if (wid == 15) bar_arrive(7, NT); else bar_sync(7, NT);
    if (tid == 480) {
#pragma unroll 1
      for (int c = 4; c < 14; c++) {
        if (c >= WIN) mbar_wait(BAR_C + (c < 8 ? c - WIN : HW0) * 8, 0);
        if (c < 8) load_idx(c); else { mbar_expect(BAR_C + c * 8, 8192); tma_load(A_PT + (c - 8) * 8192, tmb + TM_H, cta * p.NPC + (c - 8) * 64, BAR_C + c * 8); }
      }
    }
    if (tid == 448) {
      mbar_expect(BAR_W, 2 * 8192 + 2048 + 256);
      tma_load(A_W, tmb + TM_WE, 64, BAR_W); tma_load(A_W + 8192, tmb + TM_WE, 0, BAR_W); tma_load(A_W3, tmb + TM_W3, 129, BAR_W);
      bulk_load(A_WD, p.we + 128 * 64, 128, BAR_W); bulk_load(A_WD + 128, p.wx, 128, BAR_W);
    }
    __syncwarp();
  }

  const int w = wid & 3;
  const uint32_t frag = (w * 16 + (lane & 15)) * 128 + (((lane >> 4) ^ (lane & 7)) << 4), pa = A_POSH + (w * 16 + g8) * 8 + q * 2;
  float a0[32], a1[32];
  float mx = 0.f;
  auto mma = [&](float (&acc)[32], int b, int blk) {
    const uint64_t da = DHI | ((A_PT + blk * 8192) >> 4), db = DHI | ((A_W + b * 8192) >> 4);
    wg_fence();
    ss64<0>(acc, da, db); ss64<1>(acc, da + 2, db + 128); ss64<1>(acc, da + 4, db + 256); ss64<1>(acc, da + 6, db + 384);
    wg_commit();
  };
  auto epi = [&](float (&acc)[32], int b, int blk) {
    uint32_t o[16];
#pragma unroll
    for (int j = 0; j < 16; j++) o[j] = pack_f16(acc[2 * j], acc[2 * j + 1]);
    if (b) {
#pragma unroll
      for (int j = 0; j < 32; j++) mx = fmaxf(mx, fabsf(acc[j]));
    } else {
#pragma unroll
      for (int r = 0; r < 2; r++) {
        const uint32_t T = __byte_perm(lds16(pa + blk * 512 + r * 64), 0, 0x4140);
#pragma unroll
        for (int j = 0; j < 4; j++) o[2 * j + r] &= 0xFFFCFFFCu;
        const uint32_t S = decode(o[r], o[2 + r], o[4 + r], o[6 + r]);
        const uint32_t X = (T - S) & 255, Y = X | ((T - ((S + X) & 0xFFFF0000u)) & 0x00FF0000u);
#pragma unroll
        for (int j = 0; j < 4; j++) o[2 * j + r] |= (Y >> (2 * j)) & 0x00030003u;
      }
    }
    const uint32_t a = (b ? A_PT : A_QS) + blk * 8192 + frag;
#pragma unroll
    for (int j = 0; j < 4; j++) stsm4(a ^ (j << 5), o[4 * j], o[4 * j + 1], o[4 * j + 2], o[4 * j + 3]);
  };
  uint32_t W3[16], PB[16], WX[8];
  auto frags = [&]() {
#pragma unroll
    for (int k = 0; k < 4; k++) ldsm4t(W3[4 * k], W3[4 * k + 1], W3[4 * k + 2], W3[4 * k + 3], A_W3 + (lane & 15) * 128 + ((((lane >> 4) + 2 * k) ^ (lane & 7)) << 4));
#pragma unroll
    for (int j = 0; j < 8; j++) WX[j] = lds32(A_WD + 128 + j * 16 + q * 4);
  };
  auto p_check = [&](int blk) {
    const uint32_t pm = __reduce_max_sync(~0u, __float_as_uint(mx));
    if (pm > 0x46000000u || (pm < 0x3A800000u && blk * 64 + (w + 1) * 16 <= min(p.NPC, p.N - cta * p.NPC))) sts32(A_MISC, 1);
  };
  if (wid >= 12) {
    const int node0 = cta * p.NPC, nloc = max(0, min(p.NPC, p.N - node0));
    if (w == 3) {
      const uint32_t mh = amax_warp(whx & 0x7FFF7FFFu);
      sts32(A_WHS + lane * 4, cta < 64 ? bhalf(whx) : mh && mh < 0x3B00 ? ~0u : b2h(bhalf(whx)));
      __syncwarp();
      if (lane == 0 && cta < 128) { proxy_fence(); asm volatile("cp.async.bulk.global.shared::cta.bulk_group [%0], [%1], 128;" :: "l"(p.s->wh + cta * 32), "r"(A_WHS) : "memory"); }
      __syncwarp();
      ep++;
    }
    else {
      const int t = tid - 384;
      uint32_t ps[12], mp = 0;
#pragma unroll
      for (int k = 0; k < 4; k++) {
        ps[3 * k] = ps[3 * k + 1] = ps[3 * k + 2] = 0;
        asm volatile("{.reg .pred p; setp.lt.s32 p, %4, %5;\n @p ld.global.nc.u16 %0, [%3];\n @p ld.global.nc.u16 %1, [%3+2];\n @p ld.global.nc.u16 %2, [%3+4];}"
          : "+r"(ps[3 * k]), "+r"(ps[3 * k + 1]), "+r"(ps[3 * k + 2]) : "l"(p.pos + (size_t)(node0 + t + 96 * k) * 3), "r"(t + 96 * k), "r"(p.N - node0));
      }
      mbar_wait(BAR_W, 0);
#pragma unroll
      for (int k = 0; k < 11; k++) if (k < 10 || w < 2) { uint32_t v[4]; const uint32_t a = A_W + (t + k * 96) * 16; lds128(v, a); sts128(a, bhalf(v[0]), bhalf(v[1]), bhalf(v[2]), bhalf(v[3])); }
      const uint32_t wd = lds32(A_WD + lane * 4), md = amax_warp(wd & 0x7FFF7FFFu);
      bool bad = md - 0x3B00 > 0x680;
      if (w < 2) {
        uint32_t mw = 0;
#pragma unroll
        for (int k = 0; k < 2; k++) { uint32_t v[4]; const uint32_t a = A_W3 + (t + k * 64) * 16; lds128(v, a);
          sts128(a, b2h(bhalf(v[0])), b2h(bhalf(v[1])), b2h(bhalf(v[2])), b2h(bhalf(v[3]))); mw = amax2(amax2(amax2(amax2(mw, v[0]), v[1]), v[2]), v[3]); }
        bad |= amax_warp(mw) - 0x3B00 > 0x680;
      } else {
#pragma unroll
        for (int r = 0; r < 8; r++) sts32(A_WD2 + r * 128 + ((lane * 4) ^ (r << 4)), (r & 1) ? 0 : r == 6 ? 0xF753F753u : b2h(bhalf(wd)));
        const uint32_t x = lds32(A_WD + 128 + lane * 4), ex = min(max(amax_warp(x & 0x7FFF7FFFu) >> 7, 20u), 230u);
        const float sc = __uint_as_float((252 - ex) << 23);
        sts32(A_WD + 128 + lane * 4, pack_f16(bf_lo(x) * sc, bf_hi(x) * sc)); sts32(A_MISC + 12, (ex + 2) << 23);
      }
#pragma unroll
      for (int k = 0; k < 4; k++) {
        const int n = t + 96 * k;
        sts64(A_POSH + n * 8, pack_f16(bf_lo(ps[3 * k]), bf_lo(ps[3 * k + 1])), pack_f16(bf_lo(ps[3 * k + 2]), 1.f));
        sts16(A_POSB + n * 6, ps[3 * k]); sts16(A_POSB + n * 6 + 2, ps[3 * k + 1]); sts16(A_POSB + n * 6 + 4, ps[3 * k + 2]);
        mp = amax2(amax2(mp, ps[3 * k] | (ps[3 * k + 1] << 16)), ps[3 * k + 2]);
      }
      mp = amax_warp(mp);
      if (bad || !(bf_lo(mp) * bf_lo(mp) * bf_lo(md) < 6000.f) || (mp < 0x3B80 && (w + 1) * 32 <= nloc)) sts32(A_MISC, 1);
      proxy_fence();
      if (w == 0) STAMP(16);
      bar_arrive(3, NX + 96);
      ep++;
    }
    bar_sync(6, 128);
#pragma unroll 1
    for (int blk = 0; blk < 6; blk = max(blk + 1, 4)) {
      mbar_wait(BAR_T + blk * 8, 0);
      if (w == 0 && blk == 5) STAMP(17);
      mma(a0, 0, blk); mma(a1, 1, blk);
      asm volatile("wgmma.wait_group.sync.aligned 1;" ::: "memory"); fence_regs(a0);
      epi(a0, 0, blk);
      wg_wait0(); fence_regs(a1);
      bar_sync(6, 128);
      if (w == 3 && blk == 5) {
        bar_sync(8, NX + 32);
        if (lane == 0) {
          proxy_fence();
#pragma unroll 1
          for (int b = 0; b * 64 < nloc; b++) tma_store(tmb + TM_Q, 0, node0 + b * 64, A_QS + b * 8192);
          STAMP(18);
        }
        __syncwarp();
      }
      epi(a1, 1, blk);
    }
    p_check(0);
    frags();
    tgb = ep << 31;
  } else {
    const uint32_t acnt = A_CNT + ((tid + cta * p.NPC) & 511) * 4, tga = (ep & 63) * 0x04000400u, tgh = tga & 0xFFFF0000u;
    tgb = ep << 31;
    uint32_t d[16], oo[16], xx[16], lc[16], mxx = 0;
#pragma unroll
    for (int c = 0; c < 4; c++) {
      mbar_wait(BAR_C + c * 8, 0);
      if (c == 3) STAMP(1);
      lds128(d + 4 * c, a_dst(c) + tid * 16);
#pragma unroll
      for (int k = 4 * c; k < 4 * c + 4; k++) {
        if (tid * 16 + c * CH >= nb) d[k] = G * p.NPC;
        const uint32_t j = __umulhi(d[k], p.magic);
        xx[k] = atoms_add(A_SA + (j * 128 | ((j * 4) & 0x7C)), 258);
        oo[k] = j * 128;
      }
    }
#pragma unroll
    for (int k = 0; k < 16; k++) { oo[k] |= xx[k] & 0x7E; mxx = max(mxx, xx[k]); }
    if (mxx > tgh + 15900) {
#pragma unroll
      for (int k = 0; k < 16; k++) if (xx[k] > tgh + 15900) oo[k] = G * 128 + 64 + lane * 2;
    }
#pragma unroll
    for (int k = 0; k < 16; k++) sts16(A_SA + oo[k], (d[k] & 511) | tga);
    if (wid == 0) { bar_sync(1, NX); if (lane == 0) { proxy_fence(); tma_store(tmb + TM_XA, cta * 192, 0, A_SA); bulk_commit(); } __syncwarp(); } else bar_arrive(1, NX);
    STAMP(2);
    const uint32_t eb = tgb + ((tid * 4 + (cta & 3) * p.EPC) << 16);
#pragma unroll
    for (int c = 0; c < 4; c++) {
      mbar_wait(BAR_C + 32 + c * 8, 0);
      if (wid == 0 && c == 3) STAMP(21);
      lds128(lc + 4 * c, A_SRC + c * CH + tid * 16);
#pragma unroll
      for (int k = 4 * c; k < 4 * c + 4; k++) { lc[k] += eb + ((c * NX * 4 + (k & 3)) << 16); sts32(A_SB + oo[k] * 2, lc[k]); }
    }
    bar_sync(2, NX);
    if (tid == 0) { proxy_fence(); tma_store(tmb + TM_XB, cta * 96 + 32, 0, A_SB); bulk_commit(); p.s->ep[cta * 32] = ep; }
    __syncwarp();
    STAMP(3);
    if (mxx > tgh + 15900) {
#pragma unroll
      for (int k = 0; k < 16; k++) {
        const uint32_t j = __umulhi(d[k], p.magic), r = (xx[k] - tgh) / 258 - 62;
        if (r < 31 && j < G)
          asm volatile("st.relaxed.gpu.global.v2.u32 [%0], {%1, %2};" :: "l"(p.s->xe + (j * G + cta) * 32 + r), "r"(lc[k]), "r"((d[k] & 511) | (ep << 9)) : "memory");
      }
    }
    __syncwarp();
    constexpr int JS = 12; const int j0 = wid;
#pragma unroll
    for (int k = 0; k < 7; k++) if (k < 6 || tid < 385 * CAP / 8 + 9 - 6 * NX) sts128(A_TAB + (tid + k * NX) * 16, 0, 0, 0, 0);
    bar_sync(3, NX + 96);
    STAMP(12);
    const char* xin = (const char*)(p.s->x + cta * G * 24);
    uint32_t pk[11];
    const uint32_t rot = (lane + cta) & 31;
    auto poll_a = [&]() {
#pragma unroll
      for (int k = 0; k < 11; k++) pk[k] = ldg_poll(xin + (j0 + JS * k) * FS + rot * 4);
    };
    uint32_t xs = ~0u; uint2 xv;
    const uint32_t t0 = (wid >> 2) * BS + 128 + w * 256 + rot * 8, tx = lane ? tga : tgh;
    const uint32_t h1 = (cta & 31) * 4 + 4 + 62 * 258;
    int spin = 0;
    auto copy_b = [&]() {
      const uint32_t o = (j0 + JS * (lane >> 4)) * FS + 128 + (lane & 15) * 16, a = A_IN + ((wid >> 2) + 3 * (lane >> 4)) * BS + 128 + w * 256 + (lane & 15) * 16;
#pragma unroll
      for (int k = 0; k < 6; k++) if (k < 5 || lane < 16)
        asm volatile("cp.async.cg.shared.global.L2::cache_hint [%0], [%1], 16, %2;" :: "r"(a + k * 6 * BS), "l"(xin + o + k * 2 * JS * FS), "l"(pol_first()) : "memory");
    };
    {
      const int blk = (wid >> 2) + 1;
      mbar_wait(BAR_T + blk * 8, 0);
      if (wid == 8) STAMP(22);
      mma(a0, 0, blk); mma(a1, 1, blk);
      asm volatile("wgmma.wait_group.sync.aligned 1;" ::: "memory"); fence_regs(a0);
      epi(a0, 0, blk);
      bar_arrive(8, NX + 32);
      poll_a();
      wg_wait0(); fence_regs(a1);
      bar_sync(13 + (wid >> 2), 128);
      epi(a1, 1, blk);
      p_check(blk);
      if (wid == 8) STAMP(24);
    }
    {
      {
        for (;;) {
          uint32_t mh = 0, bad = 0;
#pragma unroll
          for (int k = 0; k < 11; k++) { pk[k] ^= tx; mh = max(mh, pk[k]); bad |= pk[k]; }
          if (!__any_sync(~0u, bad & (lane ? 0xFC00FC00u : 0xFC000000u))) {
            if (__shfl_sync(~0u, mh, 0) > h1) {
              uint32_t base = 0;
#pragma unroll
              for (int k = 0; k < 11; k++) {
                const uint32_t c = (max(__shfl_sync(~0u, pk[k], 0), h1) - h1) / 258;
                if (lane - base < c) xs = (j0 + JS * k) * 32 + lane - base;
                base += c;
              }
              if (base > 31) { sts32(A_MISC, 1); xs = ~0u; }
              if (xs != ~0u) xv = ldg_poll2(p.s->xe + cta * G * 32 + xs);
              __syncwarp();
            }
            break;
          }
          if (++spin > 2000000) __trap();
          poll_a();
        }
        STAMP(14); if (wid == 8) STAMP(25);
        uint32_t r0[11], r1[11];
#pragma unroll
        for (int k = 0; k < 11; k++) {
          if (lane == 0) pk[k] = (512 + rot) * 0x10001u;
          r0[k] = atoms_add(A_CNT + (pk[k] & 0xFFFF) * 4, 2);
          r1[k] = atoms_add(A_CNT + (pk[k] >> 16) * 4, 2);
        }
#pragma unroll
        for (int k = 0; k < 11; k++) { sts16(min(r0[k], A_IN - 2), t0 + 3 * k * BS); sts16(min(r1[k], A_IN - 2), t0 + 3 * k * BS + 4); }
        if (wid == 8) STAMP(26);
      }
    }
    if (tid == 0) { asm volatile("cp.async.bulk.wait_group.read 0;" ::: "memory"); mbar_arrive(BAR_X); }
    __syncwarp();
    mbar_wait(BAR_X, 0);
    copy_b();
    STAMP(4);
    if (xs != ~0u) {
      for (int i = 0; (((xv.x ^ tgb) >> 31) | ((xv.y >> 9) ^ (ep & 0x7FFFFF))) && i < 2000000; i++) xv = ldg_poll2(p.s->xe + cta * G * 32 + xs);
      const uint32_t n = atoms_add(A_XC + (xs >> 7) * 4, 4), t = (xs >> 7) * BS + 4 + min(n, 120u);
      if (n > 120) sts32(A_MISC, 1);
      sts16(min(atoms_add(A_CNT + (xv.y & 511) * 4, 2), A_IN - 2), t);
      sts32(A_IN + t, xv.x);
    }
    __syncwarp();
    bar_sync(4, NX);
    STAMP(5);
    {
      const uint32_t dg = (lds32(acnt) - (A_TAB + tid * (CAP * 2))) >> 1;
      const uint32_t dr = atoms_add(A_DH + min(dg, 63u) * 4, 1);
      bar_sync(5, NX);
      uint32_t hb, ha; lds64(hb, ha, A_DH + (62 - 2 * lane) * 4);
      uint32_t inc = ha + hb;
#pragma unroll
      for (int o = 1; o < 32; o <<= 1) { const uint32_t y = __shfl_up_sync(~0u, inc, o); if (lane >= o) inc += y; }
      const uint32_t idx = 63 - min(dg, 63u);
      const uint32_t e2 = __shfl_sync(~0u, (inc - hb) | ((inc - hb - ha) << 16), idx >> 1);
      const uint32_t pos = ((idx & 1) ? (e2 & 0xFFFF) : (e2 >> 16)) + dr;
      sts16(A_ROWS + pos * 2, tid);
      if (!(pos & 7)) sts32(A_LEN + (pos >> 1), max(1u, (dg + 1) >> 1));
      if (dg > CAP) sts32(A_MISC, 1);
    }
    STAMP(6);
    if (tid == 0) sts32(A_IN, 0xFFFF);
    for (;;) {
      asm volatile("cp.async.wait_all;" ::: "memory");
      __syncwarp();
      uint32_t bad = 0;
#pragma unroll
      for (int k = 0; k < 11; k++) { uint32_t x, y; lds64(x, y, A_IN + t0 + 3 * k * BS); bad |= (x ^ tgb) | (y ^ tgb); }
      if (!__any_sync(~0u, bad >> 31) || ++spin > 2000000) break;
      copy_b();
    }
    frags();
    STAMP(7);
  }
  if (wid == 15) {
    bar_arrive(11, NT);
    if (lane == 0) { bulk_commit(); asm volatile("cp.async.bulk.wait_group 0;" ::: "memory"); }
    __syncwarp();
    if (lane < NREP) asm volatile("red.relaxed.gpu.global.add.u32 [%0], 1;" :: "l"(p.s->cnt + lane * 32) : "memory");
    if (lane == 0) {
      STAMP(19);
      const uint32_t nbe = (p.E / G) & ~15u;
#pragma unroll 1
      for (int i = 0; i < PFA; i++)
        if (nbe) asm volatile("cp.async.bulk.prefetch.L2.global [%0], %1;" :: "l"((const char*)p.ea + (size_t)(i * G + cta) * nbe), "r"(nbe) : "memory");
      uint32_t c; int spin = 0;
      do asm volatile("ld.acquire.gpu.global.u32 %0, [%1];" : "=r"(c) : "l"(p.s->cnt + (cta % NREP) * 32) : "memory"); while ((int)(c - ep * G) < 0 && ++spin < 20000000);
      mbar_arrive(BAR_Q);
      STAMP(20);
    }
    __syncwarp();
  }
  uint32_t A2[4];
  const uint32_t ring = 4096 + wid * 4096, ering = (wid < 8 ? 69632 : A_E3 - 8 * 1536) + wid * 1536;
  const int oc = lane >> 3;
  const int r7 = lane & 7, ro = r7 >> 1, ri = 2 * (oc & 1) + (r7 & 1);
  uint64_t qp0 = (uint64_t)p.s->q + ((r7 ^ (2 * oc)) << 4), qp1 = qp0 ^ 16, epp = (uint64_t)p.ea + (((lane ^ oc) & 1) << 4) - (tgb >> 11);
  uint32_t dq = ring + oc * 512 + r7 * 16, de = ering + ((lane * 16) ^ ((oc >> 1) * 64));
  uint32_t rq = ring + (4 * ro + ri) * 128 + (((oc >> 1) ^ r7) << 4), re = ering + ro * 128 + ((ri ^ (2 * (ro >> 1))) << 5) + ((((oc >> 1) ^ ro) & 1) << 4);
  A2[0] = (g8 >> 1) == q ? ((g8 & 1) ? 0x3C000000u : 0x3C00u) : 0;
  A2[0] += lds32(A_MISC + 8); A2[1] = A2[0] + lds32(A_MISC + 8);
  asm volatile("" : "+l"(qp0), "+l"(qp1), "+l"(epp), "+r"(dq), "+r"(de), "+r"(rq), "+r"(re));
  bar_sync(wid < 15 ? 11 : 12, wid < 15 ? NT : 64);
  if (wid == 14) bar_arrive(12, 64);
  STAMP(13);
  if (__any_sync(~0u, lds32(A_MISC))) { sts32(A_MISC + 12, dq ^ de ^ rq ^ re ^ (uint32_t)qp0 ^ (uint32_t)qp1 ^ (uint32_t)(epp ^ (epp >> 32)) ^ A2[1]); __syncthreads(); slow_path(p); return; }

  uint32_t MS[8], acc[16], m[16], yh[8], A1[4], OP, TA, D = 0, U = 0, tt, tn, rec, rn, sl;
  re += lds32(A_MISC) + 1024 - ering; de += lds32(A_MISC) + 1024 - re; const uint32_t rtop = re + lds32(A_MISC);
  uint64_t pol;
  asm("createpolicy.range.global.L2::evict_normal.L2::evict_first.b64 %0, [%1], %2, %3;" : "=l"(pol) : "l"(p.ea), "r"(p.E * PFA), "r"(p.E * 32));
  const uint32_t eru = __reduce_max_sync(~0u, ering);
  const uint32_t zr = p.force_slow;
  uint32_t rk[4], ql1 = (uint32_t)qp1;
#pragma unroll
  for (int k = 0; k < 4; k++) rk[k] = (rq ^ (k * 32)) + lds32(A_MISC);
  uint32_t mk, ln, x1, x2, x3, x4, x5;
  auto lane_id = [&]() { uint32_t l; asm volatile("mov.u32 %0, %%laneid;" : "=r"(l)); return l; };
  auto nodes = [&](uint32_t r) {
    uint32_t t; asm volatile("mov.u32 %0, %%tid.x;" : "=r"(t));
    const uint32_t sc = p.sched[__shfl_sync(~0u, t >> 5, 0)];
    return lds16(A_ROWS + (sc & 63) * 16 + r * 2) | (lds16(A_ROWS + ((sc >> 6) & 63) * 16 + r * 2) << 10) | (lds16(A_ROWS + (sc >> 12) * 16 + r * 2) << 20);
  };
  auto lswitch = [&]() {
    TA = A_TAB + (x1 & 0xFFFF); x1 = __byte_perm(x1, 384 * CAP * 2, 0x5432);
    if (ln) mk |= 32u << (ln & 255);
    else {
      if (atoms_incp(A_MISC + 4, lane_id() == 0) == 31) {
        proxy_fence();
        mbar_expect(BAR_U, 16384);
#pragma unroll
        for (int k = 0; k < 2; k++)
          asm volatile("cp.async.bulk.tensor.2d.shared::cluster.global.mbarrier::complete_tx::bytes [%0], [%1, {0, %3}], [%2];" :: "r"(A_TAB + k * 8192), "l"(tmb + TM_WH), "r"(BAR_U), "r"(k * 64) : "memory");
      }
      __syncwarp();
    }
    ln >>= 8;
  };
  auto pload = [&](uint32_t a) {
#pragma unroll
    for (int k = 0; k < 4; k++) ldsm4t(PB[4 * k], PB[4 * k + 1], PB[4 * k + 2], PB[4 * k + 3], a ^ (k << 5));
  };
  auto flush = [&](int hf) {
    stsm4(((x4 & 0xFFFF) << 4) ^ (hf << 6), MS[4 * hf], MS[4 * hf + 1], MS[4 * hf + 2], MS[4 * hf + 3]);
    if (hf) { x3 = __byte_perm(x3, hadd(U, U >> 16), 0x5410); U = 0; x4 = __byte_perm(x4, 0, 0x1032); }
#pragma unroll
    for (int j = 4 * hf; j < 4 * hf + 4; j++) MS[j] = 0;
  };
  auto look1 = [&]() { asm volatile("ld.volatile.shared.u16 %0, [%1];" : "=r"(tn) : "r"(TA) : "memory"); asm volatile("add.u32 %0, %0, 4;" : "+r"(TA)); };
  auto look2 = [&](uint32_t tn) {
    asm volatile("ld.volatile.shared.u32 %0, [%1];" : "=r"(rn) : "r"(A_IN + tn) : "memory");
    tt = __umulhi(tn, 3728271u) * p.EPC4 + (rn >> 16); rn &= 0xFFFF;
    if (ABL & 1) tt = (tt & 0x1FFFF) + 65536;
  };
  auto issue_q = [&](uint32_t rec) {
#pragma unroll
    for (int i = 0; i < 4; i++)
      if (ABL & 2) asm volatile("{.reg .b64 a; .reg .pred p, l; setp.eq.u32 p, %2, 0xFFFF; setp.ge.u32 l, %3, 8; mad.wide.u32 a, %2, 128, %1;\n @l cp.async.cg.shared.global [%0], [a], 16, p;}"
        :: "r"(dq + i * 128), "l"((i & 1) ? (qp0 & ~0xFFFFFFFFull) | ql1 : qp0), "r"(__shfl_sync(~0u, rec, 2 * i, 8)), "r"(zr) : "memory");
      else asm volatile("{.reg .b64 a; .reg .pred p; setp.eq.u32 p, %2, 0xFFFF; mad.wide.u32 a, %2, 128, %1;\n cp.async.cg.shared.global [%0], [a], 16, p;}"
        :: "r"(dq + i * 128), "l"((i & 1) ? (qp0 & ~0xFFFFFFFFull) | ql1 : qp0), "r"(__shfl_sync(~0u, rec, 2 * i, 8)) : "memory");
    asm volatile("cp.async.commit_group;" ::: "memory");
    dq ^= 2048;
  };
  auto issue_e = [&](uint32_t a, uint32_t rn, uint32_t tt) {
    if (ABL & 2) asm volatile("{.reg .b64 a; .reg .pred p, l; setp.eq.u32 p, %3, 0xFFFF; setp.ge.u32 l, %5, 8; mad.wide.u32 a, %2, 32, %1;\n @l cp.async.cg.shared.global.L2::cache_hint [%0], [a], 16, p, %4;}"
      :: "r"(a), "l"(epp), "r"(tt), "r"(rn), "l"(pol), "r"(zr) : "memory");
    else asm volatile("{.reg .b64 a; .reg .pred p; setp.eq.u32 p, %3, 0xFFFF; mad.wide.u32 a, %2, 32, %1;\n cp.async.cg.shared.global.L2::cache_hint [%0], [a], 16, p, %4;}"
      :: "r"(a), "l"(epp), "r"(tt), "r"(rn), "l"(pol) : "memory");
  };
  auto act = [&](const uint32_t* y, int k) {
#pragma unroll
    for (int i = 0; i < 4; i++) { m[4 * k + i] = hsilu(y[i]); MS[2 * k + (i >> 1)] = hadd(MS[2 * k + (i >> 1)], m[4 * k + i]); }
  };
  auto cfin = [&](uint32_t d) {
    uint32_t c0_ = 0, c1_ = 0;
#pragma unroll
    for (int k = 0; k < 4; k++) { const int kk = (VAR & 32) ? k : k ^ 2; hmma(c0_, c1_, m + 4 * kk, WX[2 * kk], WX[2 * kk + 1]); }
    U = hfma(__byte_perm(c0_, c1_, 0x5410), d, U);
  };
  auto events = [&]() {
    if (mk & 1) flush(1);
    if (mk & 2) { flush(0); pload((x5 & 0xFFFF) << 4); x5 >>= 16; OP = __byte_perm(x3, 0, 0x1010); x3 >>= 16; }
    if (mk & 32) lswitch();
    if (mk < 16) {
      rec = x2 & 0xFFFF; x2 >>= 16;
      qp0 = (uint64_t)p.h + (qp0 & 127); ql1 = (uint32_t)qp0 ^ 16;
    }
  };
  auto step = [&](uint32_t st) {
    asm volatile("cp.async.wait_group 1;" ::: "memory");
    uint32_t E[4];
    ldsm4(E, re + eru);
#pragma unroll
    for (int k = 0; k < 4; k++) ldsm4(acc + 4 * k, rk[k] + st);
    look2(tn);
    issue_q(rec);
    issue_e(re + de, rn, tt); rec = rn;
    look1();
    re = __viaddmin_u32(re, 0u - 512, rtop);
    if (ABL & 4) { U ^= (E[0] ^ acc[0] ^ acc[4] ^ acc[8] ^ acc[12]) & zr; return; }
#pragma unroll
    for (int i = 0; i < 4; i++) A1[i] = pack_f16(__uint_as_float(__byte_perm(E[i], 0, 0x1044)), bf_hi(E[i]));
    const uint32_t Sa = decode(acc[0], acc[2], acc[4], acc[6]), Sb = decode(acc[1], acc[3], acc[5], acc[7]);
    const uint32_t Dp = D;
    D = hsub(OP, __byte_perm(Sa, Sb, 0x6420));
    const __half2 d = *(const __half2*)&D, x = __hmul2(d, d), y = __hmul2(__high2half2(d), __high2half2(d));
    A2[2] = *(const uint32_t*)&x; A2[3] = *(const uint32_t*)&y;
    if (VAR & 1) yh[4] |= A1[3] & zr;
    if (VAR & 2) yh[6] |= A2[3] & zr;
    act(yh, 2); act(yh + 4, 3);
#pragma unroll
    for (int j = 0; j < 8; j++) { hmma(acc[2 * j], acc[2 * j + 1], A1, W3[2 * j], W3[2 * j + 1]); hmma(acc[2 * j], acc[2 * j + 1], A2, PB[2 * j], PB[2 * j + 1]); }
    if (VAR & 4) m[(VAR & 32) ? 0 : 8] |= acc[0] & zr;
    cfin(Dp);
    if (VAR & 8) acc[6] |= acc[14] & zr;
    if (VAR & 16) acc[7] |= acc[10] & zr;
    if (VAR & 64) acc[5] |= acc[8] & zr;
    if (VAR & 128) acc[3] |= tt & zr;
    if (VAR & 256) acc[6] |= U & zr;
    if (VAR & 512) acc[2] |= m[15] & zr;
    if (VAR & 1024) acc[4] |= acc[12] & zr;
    act(acc, 0); act(acc + 4, 1);
#pragma unroll
    for (int i = 0; i < 8; i++) yh[i] = acc[8 + i];
  };
#pragma unroll
  for (int i = 0; i < 8; i++) { m[i] = 0; yh[i] = 0; MS[i] = 0; A1[i & 3] = 0; }
  { const uint32_t sc = p.sched[wid], g0 = sc & 63, g1 = (sc >> 6) & 63, g2 = sc >> 12;
    TA = A_TAB + lds16(A_ROWS + g0 * 16 + oc * 4 + (lane & 2)) * (CAP * 2) + ((lane >> 1) & 2);
    const uint32_t nd3 = nodes(r7);
    ln = __reduce_max_sync(~0u, lds32(A_LEN + g0 * 4) | (lds32(A_LEN + g1 * 4) << 8) | (lds32(A_LEN + g2 * 4) << 16));
    mk = 2u << max(ln & 255, 4u); ln >>= 8;
    uint32_t t3[3], ra, rb;
#pragma unroll
    for (int k = 0; k < 3; k++) { look1(); t3[k] = tn; }
    look1();
    look2(t3[0]); ra = rn; const uint32_t ta = tt;
    look2(t3[1]); rb = rn; const uint32_t tb = tt;
    look2(t3[2]);
    issue_e(re + de, ra, ta); issue_e(re + de - 512, rb, tb);
    mbar_wait(BAR_Q, 0);
    STAMP(8);
    issue_q(ra);
    auto prow = [&](int g) { const uint32_t nd = (nd3 >> (10 * g)) & 1023; return ((lane & 8) ? A_WD2 / 16 + r7 * 9 : A_PT / 16 + nd * 8 + (nd & 7)) ^ (lane >> 4); };
    auto mrow = [&](int g) { const uint32_t nd = (nd3 >> (10 * g)) & 1023; return A_PT / 16 + nd * 8 + (oc ^ (nd & 7)); };
    const uint32_t gn = __shfl_sync(~0u, nd3, g8);
    auto opos = [&](int g) { return lds16(A_POSH + ((gn >> (10 * g)) & 1023) * 8 + q * 2); };
    pload(prow(0) << 4); OP = opos(0) * 0x10001;
    issue_q(rb); issue_e(re + de - 1024, rn, tt); rec = rn;
    const uint32_t sn = __shfl_sync(~0u, nd3, 2 * oc + ((lane >> 1) & 1)), n0 = cta * p.NPC + ((sn >> ((lane & 4) ? 10 : 0)) & 1023), n1 = cta * p.NPC + (sn >> 20);
    x1 = (((sn >> 10) & 1023) | ((sn >> 20) << 16)) * (CAP * 2) + ((lane >> 1) & 2) * 0x10001;
    x3 = opos(1) | (opos(2) << 16); x4 = mrow(0) | (mrow(1) << 16); x5 = prow(1) | (prow(2) << 16);
    x2 = (n0 < p.N ? n0 : 0xFFFF) | ((n1 < p.N && !(lane & 4) ? n1 : 0xFFFF) << 16);
  }
  sl = 2048;
#pragma unroll 1
  do {
    if ((mk & 35) || mk < 16) events();
    sl ^= 2048; asm volatile("shr.u32 %0, %0, 1;" : "+r"(mk)); step(sl);
  } while (mk >= 4);
  sl += lds32(A_MISC); rq = rk[0] + lds32(A_MISC); dq = (dq + lds32(A_MISC)) & ~2048u;
  if (mk & 1) flush(1);
  STAMP(9);
  {
    int cta; asm volatile("mov.u32 %0, %%ctaid.x;" : "=r"(cta));
    const uint32_t l = lane_id(), node0 = cta * p.NPC; const int nloc = min(p.NPC, p.N - (int)node0);
    constexpr uint64_t dW = DHI | (A_TAB >> 4);
    float y1[32], y2[32];
    uint32_t H[16], po[3];
    asm volatile("cp.async.wait_group 1;" ::: "memory");
    __syncwarp();
    { const uint32_t a = (((l & 8) ? x4 >> 16 : x4 & 0xFFFF) ^ (l >> 3) ^ (l >> 4)) << 4;
#pragma unroll
      for (int k = 0; k < 4; k++) { ldsm4(acc + 4 * k, a ^ (k << 5)); ldsm4(H + 4 * k, (rq ^ (k * 32)) + (sl ^ 2048)); } }
    mbar_wait(BAR_U, 0);
    STAMP(10);
    wg_fence();
    rh64<0>(y1, acc, dW + 512); rh64<1>(y1, acc + 4, dW + 640); rh64<1>(y1, acc + 8, dW + 768); rh64<1>(y1, acc + 12, dW + 896);
    rs64<1>(y1, H, dW); rs64<1>(y1, H + 4, dW + 128); rs64<1>(y1, H + 8, dW + 256); rs64<1>(y1, H + 12, dW + 384);
    wg_commit();
    const uint32_t nd3 = nodes(l & 7);
    act(yh, 2); act(yh + 4, 3); cfin(D);
    { const uint32_t gn = __shfl_sync(~0u, nd3, l >> 2), a = A_POSH + (l & 3) * 2;
      sts16(a + (gn & 1023) * 8, x3); sts16(a + ((gn >> 10) & 1023) * 8, x3 >> 16); sts16(a + (gn >> 20) * 8, hadd(U, U >> 16)); }
    __syncwarp();
    if (l == 0) mbar_arrive(BAR_A);
    asm volatile("cp.async.wait_group 0;" ::: "memory");
    __syncwarp();
    wg_wait0(); fence_regs(y1);
#pragma unroll
    for (int k = 0; k < 4; k++) ldsm4(H + 4 * k, (rq ^ (k * 32)) + sl);
#pragma unroll
    for (int j = 0; j < 8; j++) acc[2 * j] = MS[j];
    wg_fence();
    rh64<0>(y2, acc, dW + 512); rh64<1>(y2, acc + 4, dW + 640); rh64<1>(y2, acc + 8, dW + 768); rh64<1>(y2, acc + 12, dW + 896);
    rs64<1>(y2, H, dW); rs64<1>(y2, H + 4, dW + 128); rs64<1>(y2, H + 8, dW + 256); rs64<1>(y2, H + 12, dW + 384);
    wg_commit();
    const float ov = y1[0] * y1[2];
    auto fin = [&](uint32_t x, float a, float b) { return badd(x, pack_bf16(silu(a), silu(b))); };
#pragma unroll
    for (int k = 0; k < 4; k += 2) {
      const uint32_t a = (rq ^ (k * 32)) + (sl ^ 2048); uint32_t x[8];
      ldsm4(x, a); ldsm4(x + 4, a ^ 32);
#pragma unroll
      for (int j = 0; j < 8; j++) x[j] = fin(x[j], y1[8 * k + 2 * j], y1[8 * k + 2 * j + 1]);
      stsm4(a, x[0], x[1], x[2], x[3]); stsm4(a ^ 32, x[4], x[5], x[6], x[7]);
    }
    { const uint32_t n0 = __shfl_sync(~0u, nd3, (l >> 2) & 6), n1 = __shfl_sync(~0u, nd3, ((l >> 2) & 6) | 1);
#pragma unroll
      for (int g = 0; g < 3; g++) po[g] = ((n0 >> (10 * g)) & 1023) | (((n1 >> (10 * g)) & 1023) << 16); }
    const uint64_t ob = (uint64_t)(p.out + (size_t)node0 * 64) + (((l & 7) ^ ((l >> 2) & 6)) << 4);
    auto put = [&](uint32_t a, uint32_t nn) {
      uint32_t v[8]; lds128(v, a); lds128(v + 4, a + 128);
#pragma unroll
      for (int i = 0; i < 2; i++)
        asm volatile("{.reg .pred p; .reg .b64 a; setp.lt.s32 p, %0, %1; mad.wide.u32 a, %0, 128, %2; @p st.global.v4.u32 [a], {%3,%4,%5,%6};}"
          :: "r"(i ? nn >> 16 : nn & 0xFFFF), "r"(nloc), "l"(ob ^ (i << 4)), "r"(v[4 * i]), "r"(v[4 * i + 1]), "r"(v[4 * i + 2]), "r"(v[4 * i + 3]) : "memory");
    };
    wg_wait0(); fence_regs(y2);
    __syncwarp();
    put(dq + (sl ^ 2048), po[0]); put(dq + 256 + (sl ^ 2048), po[1]);
    bool bad = !(fabsf(ov * y2[0] * 0.f) < 1.f);
#pragma unroll
    for (int j = 0; j < 16; j += 2) H[j] = fin(H[j], y2[2 * j], y2[2 * j + 1]);
#pragma unroll
    for (int k = 0; k < 4; k++) stsm4((rq ^ (k * 32)) + sl, H[4 * k], H[4 * k + 1], H[4 * k + 2], H[4 * k + 3]);
    __syncwarp();
    put(dq + sl, po[2]);
    const uint32_t c = __shfl_sync(~0u, atoms_incp(A_MISC + 8, l == 0), 0);
    if (c < 6) {
      mbar_wait(BAR_A, 0);
      uint32_t x[6];
#pragma unroll
      for (int k = 0; k < 6; k++) {
        const uint32_t i = c * 192 + k * 32 + l, u = lds16(A_POSH + i * 2 + i / 3 * 2);
        bad |= (u & 0x7C00) == 0x7C00;
        x[k] = pack_bf16(fmaf(__half2float(__ushort_as_half(u)), __uint_as_float(lds32(A_MISC + 12)), bf_lo(lds16(A_POSB + i * 2))), 0.f);
      }
      uint16_t* op = p.out + (size_t)p.N * 64 + (size_t)node0 * 3 + c * 192 + l;
#pragma unroll
      for (int k = 0; k < 6; k++)
        asm volatile("{.reg .pred p; setp.lt.s32 p, %0, %1; @p st.global.u16 [%2], %3;}" :: "r"(c * 192 + k * 32 + l), "r"(nloc * 3), "l"(op + k * 32), "h"((uint16_t)x[k]) : "memory");
    }
    if (__syncthreads_or(bad) && !ABL) { slow_path(p); return; }
  }
  STAMP(11);
}

}

typedef CUresult (*EncodeFn)(CUtensorMap*, CUtensorMapDataType, cuuint32_t, void*, const cuuint64_t*, const cuuint64_t*, const cuuint32_t*, const cuuint32_t*,
                             CUtensorMapInterleave, CUtensorMapSwizzle, CUtensorMapL2promotion, CUtensorMapFloatOOBfill);

extern "C" void kernel_launch(void* const* d_in, const int* in_sizes, int n_in, void* d_out, int out_size) {
  Params p; Maps maps;
  p.h = (const uint16_t*)d_in[0]; p.pos = (const uint16_t*)d_in[1]; p.ea = (const uint16_t*)d_in[2];
  p.src = (const int*)d_in[3]; p.dst = (const int*)d_in[4];
  p.we = (const uint16_t*)d_in[5]; p.wx = (const uint16_t*)d_in[6]; p.wh = (const uint16_t*)d_in[7];
  p.out = (uint16_t*)d_out;
  p.N = in_sizes[0] / 64; p.E = in_sizes[3];
  p.NPC = (p.N + G - 1) / G;
  p.EPC = ((p.E + G * 4 - 1) / (G * 4)) * 4;
  p.magic = (uint32_t)((1ull << 32) / (uint64_t)p.NPC) + 1;
  const uint32_t sched[16] = {0x27848, 0x2a50b, 0x28904, 0x2d8c1, 0x2fb80, 0x2b7c3, 0x26786, 0x1c5d3, 0x2c802, 0x22745, 0x1b609, 0x29387, 0x1654f, 0x2530a, 0x1944d, 0x1a490};
  for (int i = 0; i < 16; i++) p.sched[i] = sched[i];
  p.EPC4 = p.EPC * 4;
  uint64_t al = (uint64_t)d_out;
  for (int i = 0; i < 8; i++) if (i != 1) al |= (uint64_t)d_in[i];
  int dev = 0, sms = 0;
  cudaGetDevice(&dev); cudaDeviceGetAttribute(&sms, cudaDevAttrMultiProcessorCount, dev);
  p.force_slow = sms < G || (al & 127) || (p.E & 3) || p.NPC > 384 || p.NPC < 2 || p.EPC > 6144;
  cudaGetSymbolAddress((void**)&p.s, g_s);
  void* fn = nullptr; cudaDriverEntryPointQueryResult qr;
  cudaGetDriverEntryPoint("cuTensorMapEncodeTiled", &fn, cudaEnableDefault, &qr);
  auto mk = [&](CUtensorMap* tm, void* base, int rows, int box) {
    const cuuint64_t dim[2] = {64, (cuuint64_t)rows}, str[1] = {128}; const cuuint32_t bx[2] = {64, (cuuint32_t)box}, es[2] = {1, 1};
    ((EncodeFn)fn)(tm, CU_TENSOR_MAP_DATA_TYPE_BFLOAT16, 2, base, dim, str, bx, es, CU_TENSOR_MAP_INTERLEAVE_NONE, CU_TENSOR_MAP_SWIZZLE_128B,
                   CU_TENSOR_MAP_L2_PROMOTION_NONE, CU_TENSOR_MAP_FLOAT_OOB_FILL_NONE);
  };
  mk(&maps.m[TM_H / 128], d_in[0], p.N, 64); mk(&maps.m[TM_WE / 128], d_in[5], 145, 64); mk(&maps.m[TM_WH / 128], p.s->wh, 128, 64);
  mk(&maps.m[TM_Q / 128], p.s->q, p.N, 64);
  mk(&maps.m[TM_W3 / 128], d_in[5], 145, 16);
  for (int k = 0; k < 2; k++) {
    const cuuint64_t dim[2] = {(cuuint64_t)G * (192 >> k), (cuuint64_t)G}, str[1] = {(cuuint64_t)G * FS}; const cuuint32_t bx[2] = {64, G}, es[2] = {1, 1};
    ((EncodeFn)fn)(&maps.m[TM_XA / 128 + k], k ? CU_TENSOR_MAP_DATA_TYPE_UINT32 : CU_TENSOR_MAP_DATA_TYPE_UINT16, 2, p.s->x, dim, str, bx, es, CU_TENSOR_MAP_INTERLEAVE_NONE,
                   CU_TENSOR_MAP_SWIZZLE_NONE, CU_TENSOR_MAP_L2_PROMOTION_NONE, CU_TENSOR_MAP_FLOAT_OOB_FILL_NONE);
  }
  cudaFuncSetAttribute(egnn_kernel, cudaFuncAttributeMaxDynamicSharedMemorySize, SMEM);
  egnn_kernel<<<G, NT, SMEM>>>(p, maps);
}
```
